```python
import torch

def _softmax(x, axis=-1):
    return torch.softmax(x, dim=axis)
def _gelu(x):
    return torch.nn.functional.gelu(x, approximate="tanh")
def _silu(x):
    return torch.nn.functional.silu(x)
def _sigmoid(x):
    return torch.sigmoid(x)
def _layernorm(x, axis=-1, eps=1e-5):
    m = x.mean(dim=axis, keepdim=True)
    v = x.var(dim=axis, keepdim=True, unbiased=False)
    return (x - m) / torch.sqrt(v + eps)
def _scatter_add(tgt, idx, src, axis=0):
    return tgt.clone().index_add_(axis, idx, src)
def _segment_sum(src, seg, n):
    out = torch.zeros((n,) + src.shape[1:], dtype=src.dtype)
    return out.index_add_(0, seg, src)
def _pad(x, pw):
    flat = tuple(v for pair in reversed(pw) for v in pair)
    return torch.nn.functional.pad(x, flat)

kernel_name = 'sequential_preLN__mha_block__moe_arch_mod__prompt'

def setup_inputs():

    _w = (lambda a: (lambda t: t.to(torch.bfloat16) if t.is_floating_point() else t)(torch.as_tensor(a)))
    def _A_setup():
        B, S, D, H = 1, 2048, 640, 32
        return {
            "x": _w((lambda *s: torch.randn(*s, dtype=torch.bfloat16) * 0.05)(B, S, D)),
            "wqkv": _w((lambda *s: torch.randn(*s, dtype=torch.bfloat16) * 0.05)(D, 3 * D)),
            "wo": _w((lambda *s: torch.randn(*s, dtype=torch.bfloat16) * 0.05)(D, D)),
        }
    _A_in = _A_setup()

    def _B_setup():
        B, S, D, F, C = 1, 2048, 640, 1536, 2
        return {
            "x": _w((lambda *s: torch.randn(*s, dtype=torch.bfloat16) * 0.05)(B, S, D)),
            "w_r": _w((lambda *s: torch.randn(*s, dtype=torch.bfloat16) * 0.05)(D)),
            "w_gate": _w((lambda *s: torch.randn(*s, dtype=torch.bfloat16) * 0.05)(D, F)),
            "w_up": _w((lambda *s: torch.randn(*s, dtype=torch.bfloat16) * 0.05)(D, F)),
            "w_down": _w((lambda *s: torch.randn(*s, dtype=torch.bfloat16) * 0.05)(F, D)),
        }
    _B_in = _B_setup()

    return {
        "A_x": _A_in["x"],
        "A_wqkv": _A_in["wqkv"],
        "A_wo": _A_in["wo"],
        "B_x": _B_in["x"],
        "B_w_r": _B_in["w_r"],
        "B_w_gate": _B_in["w_gate"],
        "B_w_up": _B_in["w_up"],
        "B_w_down": _B_in["w_down"],
    }

def reference(A_x, A_wqkv, A_wo, B_x, B_w_r, B_w_gate, B_w_up, B_w_down):
    def _A_ref(x, wqkv, wo):
        B, S, D = x.shape
        H = 32
        Dh = D // H
        qkv = (lambda x, *d: x.permute(*d))((x @ wqkv).reshape(B, S, 3, H, Dh), 2, 0, 3, 1, 4)
        q, k, v = qkv[0], qkv[1], qkv[2]
        scores = torch.einsum("bhqd,bhkd->bhqk", q, k) * (Dh ** -0.5)
        p = _softmax(scores, axis=-1)
        o = torch.einsum("bhqk,bhkd->bhqd", p, v)
        return (lambda x, *d: x.permute(*d))(o, 0, 2, 1, 3).reshape(B, S, D) @ wo

    def _B_ref(x, w_r, w_gate, w_up, w_down):
        B, S, D = x.shape
        C = 2
        r = x @ w_r
        idx = torch.argsort(-r, axis=-1)[:, :C]
        idx_e = (lambda x, n, axis: torch.repeat_interleave(x, n, dim=axis))(idx.reshape(B, C, 1), D, axis=2)
        x_sel = (lambda x, i, axis: torch.take_along_dim(x, i, dim=axis))(x, idx_e, axis=1)
        g = _silu(x_sel @ w_gate)
        u = x_sel @ w_up
        y = (g * u) @ w_down
        r_sel = _sigmoid((lambda x, i, axis: torch.take_along_dim(x, i, dim=axis))(r, idx, axis=1))
        y = y * r_sel.reshape(B, C, 1)
        b_off = (torch.arange(B) * S).reshape(B, 1)
        flat_idx = (idx + b_off).reshape(B * C)
        zero = (x * 0.0).reshape(B * S, D)
        upd = _scatter_add(zero, flat_idx, y.reshape(B * C, D), axis=0)
        return x + upd.reshape(B, S, D)

    x = A_x
    h = x + _A_ref(_layernorm(x, axis=-1), A_wqkv, A_wo)
    h2 = h + _B_ref(_layernorm(h, axis=-1), B_w_r, B_w_gate, B_w_up, B_w_down)
    return h2
```

```cpp
#include <cuda_runtime.h>
#include <cuda_bf16.h>
#include <cuda.h>
#include <stdint.h>

typedef __nv_bfloat16 bf16;

constexpr int S_ = 2048, D_ = 640, H_ = 32, F_ = 1536;
constexpr int HEAD_BYTES = 256 * 384;
constexpr uint32_t POLYMASK = 0xADADu;
constexpr float QSCALE = 0.22360679774997896f * 1.4426950408889634f;

__device__ __align__(1024) uint8_t g_qkv[3 * H_ * HEAD_BYTES];
__device__ float g_kmax[H_ * 128];
__device__ __align__(16) ulonglong2 g_rowstat[S_];
__device__ __align__(16) unsigned long long g_colsum[3 * D_];
__device__ unsigned g_epoch;
__device__ __align__(1024) bf16 g_o[S_ * D_];
constexpr int XC_PART = 0;
constexpr int XC_KEYS = XC_PART + S_ * 64;
constexpr int XC_CAND = XC_KEYS + 4 * 32 * 16;
constexpr int XC_HF = XC_CAND + 32 * 2 * 2560;
constexpr int XC_BYTES = XC_HF + 2 * F_ * 2;
static_assert(XC_BYTES == 128 * 148 * 16, "K2 resets 148 x 16 bytes per CTA");
__device__ __align__(1024) uint8_t g_xc[XC_BYTES];
__device__ __align__(1024) uint8_t g_wimg[3 * D_ * F_ * 2];
__device__ __align__(1024) uint8_t g_wo_img[D_ * D_ * 2];

#define TL(k, slot) do {} while (0)
#define TLC(k, slot) do {} while (0)
__device__ __forceinline__ uint32_t smem_u32(const void* p) { return (uint32_t)__cvta_generic_to_shared(p); }
__device__ __forceinline__ uint64_t make_desc(uint32_t lo, uint32_t hi) {
    uint64_t d; asm("mov.b64 %0, {%1, %2};" : "=l"(d) : "r"(lo), "r"(hi));
    return d;
}
__device__ __forceinline__ void wg_fence() { asm volatile("wgmma.fence.sync.aligned;" ::: "memory"); }
__device__ __forceinline__ void wg_commit() { asm volatile("wgmma.commit_group.sync.aligned;" ::: "memory"); }
template<int N> __device__ __forceinline__ void wg_wait() { asm volatile("wgmma.wait_group.sync.aligned %0;" :: "n"(N) : "memory"); }
__device__ __forceinline__ void mbar_init(uint32_t bar, uint32_t cnt) { asm volatile("mbarrier.init.shared::cta.b64 [%0], %1;" :: "r"(bar), "r"(cnt)); }
__device__ __forceinline__ void mbar_expect_tx(uint32_t bar, uint32_t bytes) { asm volatile("mbarrier.arrive.expect_tx.shared::cta.b64 _, [%0], %1;" :: "r"(bar), "r"(bytes) : "memory"); }
__device__ __forceinline__ void mbar_arrive(uint32_t bar) { asm volatile("mbarrier.arrive.shared::cta.b64 _, [%0];" :: "r"(bar) : "memory"); }
__device__ __forceinline__ void mbar_arrive_cluster(uint32_t bar, uint32_t cta) {
    asm volatile("{\n.reg .b32 ra;\nmapa.shared::cluster.u32 ra, %0, %1;\n"
                 "mbarrier.arrive.shared::cluster.b64 _, [ra];\n}\n" :: "r"(bar), "r"(cta) : "memory");
}
__device__ __forceinline__ void mbar_wait(uint32_t bar, uint32_t parity) {
    asm volatile("{\n"
        ".reg .pred p;\n.reg .u32 c;\n"
        "mov.u32 c, 0;\n"
        "WAIT_LOOP:\n"
        "mbarrier.try_wait.parity.shared::cta.b64 p, [%0], %1;\n"
        "@p bra WAIT_DONE;\n"
        "add.u32 c, c, 1;\n"
        "setp.lt.u32 p, c, 0x1000000;\n"
        "@p bra WAIT_LOOP;\n"
        "trap;\n"
        "WAIT_DONE:\n"
        "}\n" :: "r"(bar), "r"(parity) : "memory");
}
__device__ __forceinline__ void mbar_wait_warp(uint32_t bar, uint32_t parity) {
    asm volatile("{\n"
        ".reg .pred p, q;\n.reg .u32 c;\n"
        "mov.u32 c, 0;\n"
        "WAIT_LOOP:\n"
        "mbarrier.try_wait.parity.shared::cta.b64 p, [%0], %1;\n"
        "vote.sync.all.pred p, p, 0xffffffff;\n"
        "@p bra.uni WAIT_DONE;\n"
        "add.u32 c, c, 1;\n"
        "setp.lt.u32 q, c, 0x1000000;\n"
        "@q bra.uni WAIT_LOOP;\n"
        "trap;\n"
        "WAIT_DONE:\n"
        "}\n" :: "r"(bar), "r"(parity) : "memory");
}
__device__ __forceinline__ void mbar_wait_cluster(uint32_t bar, uint32_t parity) {
    asm volatile("{\n"
        ".reg .pred p;\n.reg .u32 c;\n"
        "mov.u32 c, 0;\n"
        "WAIT_LOOP:\n"
        "mbarrier.try_wait.parity.acquire.cluster.shared::cta.b64 p, [%0], %1;\n"
        "@p bra WAIT_DONE;\n"
        "add.u32 c, c, 1;\n"
        "setp.lt.u32 p, c, 0x1000000;\n"
        "@p bra WAIT_LOOP;\n"
        "trap;\n"
        "WAIT_DONE:\n"
        "}\n" :: "r"(bar), "r"(parity) : "memory");
}
__device__ __forceinline__ void fence_mbar_init() { asm volatile("fence.mbarrier_init.release.cluster;" ::: "memory"); }
__device__ __forceinline__ void fence_async_smem() { asm volatile("fence.proxy.async.shared::cta;" ::: "memory"); }
__device__ __forceinline__ void bulk_g2s(uint32_t dst, const void* src, uint32_t bytes, uint32_t bar) {
    asm volatile("cp.async.bulk.shared::cluster.global.mbarrier::complete_tx::bytes [%0], [%1], %2, [%3];" :: "r"(dst), "l"(src), "r"(bytes), "r"(bar) : "memory");
}
__device__ __forceinline__ void bulk_g2s_mc(uint32_t dst, const void* src, uint32_t bytes, uint32_t bar, uint16_t mask) {
    asm volatile("cp.async.bulk.shared::cluster.global.mbarrier::complete_tx::bytes.multicast::cluster [%0], [%1], %2, [%3], %4;"
        :: "r"(dst), "l"(src), "r"(bytes), "r"(bar), "h"(mask) : "memory");
}
__device__ __forceinline__ void bulk_s2g(void* dst, uint32_t src, uint32_t bytes) {
    asm volatile("cp.async.bulk.global.shared::cta.bulk_group [%0], [%1], %2;" :: "l"(dst), "r"(src), "r"(bytes) : "memory");
}
__device__ __forceinline__ void bulk_commit() { asm volatile("cp.async.bulk.commit_group;" ::: "memory"); }
__device__ __forceinline__ void bulk_wait_all() { asm volatile("cp.async.bulk.wait_group 0;" ::: "memory"); }
__device__ __forceinline__ void prefetch_l2(const void* p, uint32_t bytes) {
    asm volatile("cp.async.bulk.prefetch.L2.global [%0], %1;" :: "l"(p), "r"(bytes) : "memory");
}
__device__ __forceinline__ void tma_2d(uint32_t dst, const CUtensorMap* tm, int c0, int c1, uint32_t bar) {
    asm volatile("cp.async.bulk.tensor.2d.shared::cluster.global.mbarrier::complete_tx::bytes [%0], [%1, {%3, %4}], [%2];"
        :: "r"(dst), "l"(tm), "r"(bar), "r"(c0), "r"(c1) : "memory");
}
__device__ __forceinline__ void tma_2d_mc(uint32_t dst, const CUtensorMap* tm, int c0, int c1, uint32_t bar, uint16_t mask) {
    asm volatile("cp.async.bulk.tensor.2d.shared::cluster.global.mbarrier::complete_tx::bytes.multicast::cluster [%0], [%1, {%3, %4}], [%2], %5;"
        :: "r"(dst), "l"(tm), "r"(bar), "r"(c0), "r"(c1), "h"(mask) : "memory");
}
__device__ __forceinline__ void tma_3d(uint32_t dst, const CUtensorMap* tm, int c0, int c1, int c2, uint32_t bar) {
    asm volatile("cp.async.bulk.tensor.3d.shared::cluster.global.mbarrier::complete_tx::bytes [%0], [%1, {%3, %4, %5}], [%2];"
        :: "r"(dst), "l"(tm), "r"(bar), "r"(c0), "r"(c1), "r"(c2) : "memory");
}
__device__ __forceinline__ void tmap_prefetch(const CUtensorMap* tm) { asm volatile("prefetch.tensormap [%0];" :: "l"(tm) : "memory"); }
__device__ __forceinline__ void cluster_arrive() { asm volatile("barrier.cluster.arrive.relaxed.aligned;" ::: "memory"); }
__device__ __forceinline__ void cluster_wait() { asm volatile("barrier.cluster.wait.acquire.aligned;" ::: "memory"); }
template<int ID, int N> __device__ __forceinline__ void named_bar() { asm volatile("bar.sync %0, %1;" :: "n"(ID), "n"(N) : "memory"); }
__device__ __forceinline__ void pdl_launch() { asm volatile("griddepcontrol.launch_dependents;" ::: "memory"); }
__device__ __forceinline__ void pdl_wait() { asm volatile("griddepcontrol.wait;" ::: "memory"); }
__device__ __forceinline__ uint4 ldg_v4(const void* p) {
    uint4 v; asm volatile("ld.relaxed.gpu.global.v4.b32 {%0,%1,%2,%3}, [%4];" : "=r"(v.x), "=r"(v.y), "=r"(v.z), "=r"(v.w) : "l"(p)); return v;
}
__device__ __forceinline__ uint32_t ldg_b32(const void* p) {
    uint32_t v; asm volatile("ld.relaxed.gpu.global.b32 %0, [%1];" : "=r"(v) : "l"(p)); return v;
}
__device__ __forceinline__ void st_tagged(void* p, float v, uint32_t tag) {
    asm volatile("st.relaxed.gpu.global.b64 [%0], %1;" :: "l"(p), "l"(((unsigned long long)tag << 32) | __float_as_uint(v)) : "memory");
}
__device__ __forceinline__ void st_tagged2(void* p, float v0, float v1, uint32_t tag) {
    asm volatile("st.relaxed.gpu.global.v2.b64 [%0], {%1, %2};" :: "l"(p), "l"(((unsigned long long)tag << 32) | __float_as_uint(v0)),
                 "l"(((unsigned long long)tag << 32) | __float_as_uint(v1)) : "memory");
}
__device__ __forceinline__ uint4 ld_tagged2(const void* p) {
    unsigned long long a, b;
    asm volatile("ld.relaxed.gpu.global.v2.b64 {%0, %1}, [%2];" : "=l"(a), "=l"(b) : "l"(p) : "memory");
    return make_uint4((uint32_t)a, (uint32_t)(a >> 32), (uint32_t)b, (uint32_t)(b >> 32));
}
__device__ __forceinline__ void stmatrix_x4(uint32_t addr, uint32_t r0, uint32_t r1, uint32_t r2, uint32_t r3) {
    asm volatile("stmatrix.sync.aligned.m8n8.x4.shared.b16 [%0], {%1, %2, %3, %4};" :: "r"(addr), "r"(r0), "r"(r1), "r"(r2), "r"(r3) : "memory");
}
__device__ __forceinline__ void named_bar_rr(int id, int n) { asm volatile("bar.sync %0, %1;" :: "r"(id), "r"(n) : "memory"); }
template<int ID, int N> __device__ __forceinline__ void named_arrive() { asm volatile("bar.arrive %0, %1;" :: "n"(ID), "n"(N) : "memory"); }
__device__ __forceinline__ void bulk_wait_read() { asm volatile("cp.async.bulk.wait_group.read 0;" ::: "memory"); }
__device__ __forceinline__ uint4 lds_v4(uint32_t a) {
    uint4 v; asm volatile("ld.shared.v4.b32 {%0,%1,%2,%3}, [%4];" : "=r"(v.x), "=r"(v.y), "=r"(v.z), "=r"(v.w) : "r"(a) : "memory"); return v;
}
__device__ __forceinline__ void sts_v4(uint32_t a, const uint4 v) {
    asm volatile("st.shared.v4.b32 [%0], {%1,%2,%3,%4};" :: "r"(a), "r"(v.x), "r"(v.y), "r"(v.z), "r"(v.w) : "memory");
}
__device__ __forceinline__ float bf_lo(uint32_t v) { return __uint_as_float(v << 16); }
__device__ __forceinline__ float bf_hi(uint32_t v) { return __uint_as_float(v & 0xffff0000u); }
__device__ __forceinline__ uint32_t pack_bf(float lo, float hi) {
    uint32_t r; asm("cvt.rn.bf16x2.f32 %0, %1, %2;" : "=r"(r) : "f"(hi), "f"(lo)); return r;
}
__device__ __forceinline__ float round_bf(float x) { return __bfloat162float(__float2bfloat16_rn(x)); }

__device__ __forceinline__ void mma_n240_ss(float (&d)[120], uint64_t da, uint64_t db, int scale_d) {
    asm volatile("{\n.reg .pred p;\nsetp.ne.b32 p, %122, 0;\n"
        "wgmma.mma_async.sync.aligned.m64n240k16.f32.bf16.bf16 "
        "{%0,%1,%2,%3,%4,%5,%6,%7,%8,%9,%10,%11,%12,%13,%14,%15,%16,%17,%18,%19,%20,%21,%22,%23,%24,%25,%26,%27,%28,%29,%30,%31,%32,%33,%34,%35,%36,%37,%38,%39,%40,%41,%42,%43,%44,%45,%46,%47,%48,%49,%50,%51,%52,%53,%54,%55,%56,%57,%58,%59,%60,%61,%62,%63,%64,%65,%66,%67,%68,%69,%70,%71,%72,%73,%74,%75,%76,%77,%78,%79,%80,%81,%82,%83,%84,%85,%86,%87,%88,%89,%90,%91,%92,%93,%94,%95,%96,%97,%98,%99,%100,%101,%102,%103,%104,%105,%106,%107,%108,%109,%110,%111,%112,%113,%114,%115,%116,%117,%118,%119}, %120, %121, p, 1, 1, 0, 1;\n}\n"
        : "+f"(d[0]), "+f"(d[1]), "+f"(d[2]), "+f"(d[3]), "+f"(d[4]), "+f"(d[5]), "+f"(d[6]), "+f"(d[7]), "+f"(d[8]), "+f"(d[9]), "+f"(d[10]), "+f"(d[11]), "+f"(d[12]), "+f"(d[13]), "+f"(d[14]), "+f"(d[15]), "+f"(d[16]), "+f"(d[17]), "+f"(d[18]), "+f"(d[19]), "+f"(d[20]), "+f"(d[21]), "+f"(d[22]), "+f"(d[23]), "+f"(d[24]), "+f"(d[25]), "+f"(d[26]), "+f"(d[27]), "+f"(d[28]), "+f"(d[29]), "+f"(d[30]), "+f"(d[31]), "+f"(d[32]), "+f"(d[33]), "+f"(d[34]), "+f"(d[35]), "+f"(d[36]), "+f"(d[37]), "+f"(d[38]), "+f"(d[39]), "+f"(d[40]), "+f"(d[41]), "+f"(d[42]), "+f"(d[43]), "+f"(d[44]), "+f"(d[45]), "+f"(d[46]), "+f"(d[47]), "+f"(d[48]), "+f"(d[49]), "+f"(d[50]), "+f"(d[51]), "+f"(d[52]), "+f"(d[53]), "+f"(d[54]), "+f"(d[55]), "+f"(d[56]), "+f"(d[57]), "+f"(d[58]), "+f"(d[59]), "+f"(d[60]), "+f"(d[61]), "+f"(d[62]), "+f"(d[63]), "+f"(d[64]), "+f"(d[65]), "+f"(d[66]), "+f"(d[67]), "+f"(d[68]), "+f"(d[69]), "+f"(d[70]), "+f"(d[71]), "+f"(d[72]), "+f"(d[73]), "+f"(d[74]), "+f"(d[75]), "+f"(d[76]), "+f"(d[77]), "+f"(d[78]), "+f"(d[79]), "+f"(d[80]), "+f"(d[81]), "+f"(d[82]), "+f"(d[83]), "+f"(d[84]), "+f"(d[85]), "+f"(d[86]), "+f"(d[87]), "+f"(d[88]), "+f"(d[89]), "+f"(d[90]), "+f"(d[91]), "+f"(d[92]), "+f"(d[93]), "+f"(d[94]), "+f"(d[95]), "+f"(d[96]), "+f"(d[97]), "+f"(d[98]), "+f"(d[99]), "+f"(d[100]), "+f"(d[101]), "+f"(d[102]), "+f"(d[103]), "+f"(d[104]), "+f"(d[105]), "+f"(d[106]), "+f"(d[107]), "+f"(d[108]), "+f"(d[109]), "+f"(d[110]), "+f"(d[111]), "+f"(d[112]), "+f"(d[113]), "+f"(d[114]), "+f"(d[115]), "+f"(d[116]), "+f"(d[117]), "+f"(d[118]), "+f"(d[119])
        : "l"(da), "l"(db), "r"(scale_d));
}

__device__ __forceinline__ void mma_n160_ss(float (&d)[80], uint64_t da, uint64_t db, int scale_d) {
    asm volatile("{\n.reg .pred p;\nsetp.ne.b32 p, %82, 0;\n"
        "wgmma.mma_async.sync.aligned.m64n160k16.f32.bf16.bf16 "
        "{%0,%1,%2,%3,%4,%5,%6,%7,%8,%9,%10,%11,%12,%13,%14,%15,%16,%17,%18,%19,%20,%21,%22,%23,%24,%25,%26,%27,%28,%29,%30,%31,%32,%33,%34,%35,%36,%37,%38,%39,%40,%41,%42,%43,%44,%45,%46,%47,%48,%49,%50,%51,%52,%53,%54,%55,%56,%57,%58,%59,%60,%61,%62,%63,%64,%65,%66,%67,%68,%69,%70,%71,%72,%73,%74,%75,%76,%77,%78,%79}, %80, %81, p, 1, 1, 0, 1;\n}\n"
        : "+f"(d[0]), "+f"(d[1]), "+f"(d[2]), "+f"(d[3]), "+f"(d[4]), "+f"(d[5]), "+f"(d[6]), "+f"(d[7]), "+f"(d[8]), "+f"(d[9]), "+f"(d[10]), "+f"(d[11]), "+f"(d[12]), "+f"(d[13]), "+f"(d[14]), "+f"(d[15]), "+f"(d[16]), "+f"(d[17]), "+f"(d[18]), "+f"(d[19]), "+f"(d[20]), "+f"(d[21]), "+f"(d[22]), "+f"(d[23]), "+f"(d[24]), "+f"(d[25]), "+f"(d[26]), "+f"(d[27]), "+f"(d[28]), "+f"(d[29]), "+f"(d[30]), "+f"(d[31]), "+f"(d[32]), "+f"(d[33]), "+f"(d[34]), "+f"(d[35]), "+f"(d[36]), "+f"(d[37]), "+f"(d[38]), "+f"(d[39]), "+f"(d[40]), "+f"(d[41]), "+f"(d[42]), "+f"(d[43]), "+f"(d[44]), "+f"(d[45]), "+f"(d[46]), "+f"(d[47]), "+f"(d[48]), "+f"(d[49]), "+f"(d[50]), "+f"(d[51]), "+f"(d[52]), "+f"(d[53]), "+f"(d[54]), "+f"(d[55]), "+f"(d[56]), "+f"(d[57]), "+f"(d[58]), "+f"(d[59]), "+f"(d[60]), "+f"(d[61]), "+f"(d[62]), "+f"(d[63]), "+f"(d[64]), "+f"(d[65]), "+f"(d[66]), "+f"(d[67]), "+f"(d[68]), "+f"(d[69]), "+f"(d[70]), "+f"(d[71]), "+f"(d[72]), "+f"(d[73]), "+f"(d[74]), "+f"(d[75]), "+f"(d[76]), "+f"(d[77]), "+f"(d[78]), "+f"(d[79])
        : "l"(da), "l"(db), "r"(scale_d));
}

#define D8(d,o) "+f"(d[o+0]), "+f"(d[o+1]), "+f"(d[o+2]), "+f"(d[o+3]), "+f"(d[o+4]), "+f"(d[o+5]), "+f"(d[o+6]), "+f"(d[o+7])
template<int SCALE_D>
__device__ __forceinline__ void mma_n64_rs(float (&d)[32], uint32_t a0, uint32_t a1, uint32_t a2, uint32_t a3, uint64_t db) {
    asm volatile("{\n"
        "wgmma.mma_async.sync.aligned.m64n64k16.f32.bf16.bf16 "
        "{%0,%1,%2,%3,%4,%5,%6,%7,%8,%9,%10,%11,%12,%13,%14,%15,"
        "%16,%17,%18,%19,%20,%21,%22,%23,%24,%25,%26,%27,%28,%29,%30,%31}, {%32,%33,%34,%35}, %36, %37, 1, 1, 0;\n}\n"
        : D8(d,0), D8(d,8), D8(d,16), D8(d,24)
        : "r"(a0), "r"(a1), "r"(a2), "r"(a3), "l"(db), "n"(SCALE_D));
}
template<int SCALE_D>
__device__ __forceinline__ void mma_n24_rs(float (&d)[12], uint32_t a0, uint32_t a1, uint32_t a2, uint32_t a3, uint64_t db) {
    asm volatile("{\n"
        "wgmma.mma_async.sync.aligned.m64n24k16.f32.bf16.bf16 "
        "{%0,%1,%2,%3,%4,%5,%6,%7,%8,%9,%10,%11}, {%12,%13,%14,%15}, %16, %17, 1, 1, 1;\n}\n"
        : "+f"(d[0]), "+f"(d[1]), "+f"(d[2]), "+f"(d[3]), "+f"(d[4]), "+f"(d[5]), "+f"(d[6]), "+f"(d[7]),
          "+f"(d[8]), "+f"(d[9]), "+f"(d[10]), "+f"(d[11])
        : "r"(a0), "r"(a1), "r"(a2), "r"(a3), "l"(db), "n"(SCALE_D));
}

constexpr int K1_STAGE = 49152, K1_NST = 4;
constexpr int K1_OFF_CS = K1_NST * K1_STAGE;
constexpr int K1_OFF_RS = K1_OFF_CS + 1024;
constexpr int K1_OFF_PART = K1_OFF_RS + 1024;
constexpr int K1_OFF_BAR = K1_OFF_PART + 256;
constexpr int K1_SMEM = K1_OFF_BAR + 128;
constexpr uint32_t KAUX0 = 0x43C03F80u, KAUX1 = 0x3B2CBFCDu;

template<int P> __device__ __forceinline__ void k1_store_pair(uint32_t sb, int nt, int mt) {
    named_bar<5 + P, 288>();
    if ((threadIdx.x & 31) < 2) {
        const int hl = 2 * P + (threadIdx.x & 31);
        bulk_s2g(g_qkv + (size_t)(nt * 12 + hl) * HEAD_BYTES + mt * 6144, sb + hl * 6144, 6144);
        bulk_commit();
    }
}

__global__ void __launch_bounds__(384, 1)
k1_qkv(const __grid_constant__ CUtensorMap tmX, const __grid_constant__ CUtensorMap tmW, const bf16* __restrict__ x, const bf16* __restrict__ W,
       const bf16* __restrict__ wo) {
    extern __shared__ __align__(1024) uint8_t smem[];
    const uint32_t sb = smem_u32(smem);
    const uint32_t barFull = sb + K1_OFF_BAR, barEmpty = barFull + 32, barStat = barFull + 64;
    const int tid = threadIdx.x, warp = tid >> 5, lane = tid & 31;
    uint32_t rank; asm("mov.u32 %0, %%cluster_ctarank;" : "=r"(rank));
    const int pair = blockIdx.x >> 1, nt = pair & 7, mt = (pair >> 3) * 2 + (int)rank;
    pdl_launch();
    if (tid == 0) TL(0, 0);

    if (warp == 8) {
        if (lane == 0) {
            tmap_prefetch(&tmX);
            tmap_prefetch(&tmW);
            for (int s = 0; s < K1_NST; s++) { mbar_init(barFull + 8 * s, 1); mbar_init(barEmpty + 8 * s, 4); }
            mbar_init(barStat, 3);
            fence_mbar_init();
            fence_async_smem();
            mbar_expect_tx(barFull, K1_STAGE);
            tma_2d(sb, &tmX, 0, mt * 128, barFull);
            for (int s = 1; s < K1_NST; s++) mbar_expect_tx(barFull + 8 * s, K1_STAGE);
        }
        __syncwarp();
        if (lane == 0) TL(0, 6);
        cluster_arrive();
        cluster_wait();
        if (lane == 0) TL(0, 7);
        if (lane == 0) {
            const int a = 2 * (int)rank;
            for (int kt = 0; kt < 10; kt++) {
                const int s = kt & 3;
                const uint32_t st = sb + s * K1_STAGE, bar = barFull + 8 * s;
                if (kt >= K1_NST) {
                    mbar_wait(barEmpty + 8 * s, ((kt >> 2) - 1) & 1);
                    mbar_expect_tx(bar, K1_STAGE);
                }
                tma_2d_mc(st + 16384 + a * 8192, &tmW, nt * 240 + a * 64, kt * 64, bar, (uint16_t)3);
                tma_2d_mc(st + 16384 + (a + 1) * 8192, &tmW, nt * 240 + (a + 1) * 64, kt * 64, bar, (uint16_t)3);
                if (kt > 0) tma_2d(st, &tmX, kt * 64, mt * 128, bar);
                TL(0, 20 + kt);
            }
        }
        __syncwarp();
        k1_store_pair<0>(sb, nt, mt);
        k1_store_pair<4>(sb, nt, mt);
        bulk_wait_read();
    } else if (warp > 8) {
        cluster_arrive();
        const int hw = warp - 9, b = blockIdx.x;
        uint4 wv[14], xv[15];
        #pragma unroll
        for (int i = 0; i < 3; i++) {
            const int p = hw + 3 * i;
            #pragma unroll
            for (int c = 0; c < 5; c++) {
                xv[i * 5 + c] = make_uint4(0, 0, 0, 0);
                if (p < 8) xv[i * 5 + c] = ldg_v4((const uint4*)(x + (size_t)(b * 16 + 2 * p + (lane >> 4)) * D_) + (lane & 15) + 16 * c);
            }
        }
        #pragma unroll
        for (int i = 0; i < 14; i++) {
            const int it = hw + 3 * i;
            wv[i] = make_uint4(0, 0, 0, 0);
            if (b < 120 && it < 40) wv[i] = ldg_v4((const uint4*)(W + (size_t)(it * 16 + (lane >> 1)) * 1920 + b * 16 + (lane & 1) * 8));
        }
        const uint32_t tag = ldg_b32(&g_epoch) + 1;
        #pragma unroll
        for (int i = 0; i < 3; i++) {
            const int p = hw + 3 * i;
            float s = 0.f;
            #pragma unroll
            for (int c = 0; c < 5; c++) {
                const uint4 v = xv[i * 5 + c];
                s += (bf_lo(v.x) + bf_hi(v.x)) + (bf_lo(v.y) + bf_hi(v.y)) + (bf_lo(v.z) + bf_hi(v.z)) + (bf_lo(v.w) + bf_hi(v.w));
            }
            #pragma unroll
            for (int o = 1; o < 16; o <<= 1) s += __shfl_xor_sync(~0u, s, o);
            const float mu = s * (1.f / D_);
            float q = 0.f;
            #pragma unroll
            for (int c = 0; c < 5; c++) {
                const uint4 v = xv[i * 5 + c];
                float d;
                d = bf_lo(v.x) - mu; q += d * d; d = bf_hi(v.x) - mu; q += d * d;
                d = bf_lo(v.y) - mu; q += d * d; d = bf_hi(v.y) - mu; q += d * d;
                d = bf_lo(v.z) - mu; q += d * d; d = bf_hi(v.z) - mu; q += d * d;
                d = bf_lo(v.w) - mu; q += d * d; d = bf_hi(v.w) - mu; q += d * d;
            }
            #pragma unroll
            for (int o = 1; o < 16; o <<= 1) q += __shfl_xor_sync(~0u, q, o);
            if (p < 8 && (lane & 15) == 0) st_tagged2(&g_rowstat[b * 16 + 2 * p + (lane >> 4)], mu, rsqrtf(q * (1.f / D_) + 1e-5f), tag);
        }
        if (tid == 288) { TL(0, 8); prefetch_l2((const uint8_t*)wo + b * 6400, 6400); }
        float cs[8];
        #pragma unroll
        for (int j = 0; j < 8; j++) cs[j] = 0.f;
        #pragma unroll
        for (int i = 0; i < 14; i++) {
            cs[0] += bf_lo(wv[i].x); cs[1] += bf_hi(wv[i].x); cs[2] += bf_lo(wv[i].y); cs[3] += bf_hi(wv[i].y);
            cs[4] += bf_lo(wv[i].z); cs[5] += bf_hi(wv[i].z); cs[6] += bf_lo(wv[i].w); cs[7] += bf_hi(wv[i].w);
        }
        #pragma unroll
        for (int j = 0; j < 8; j++) {
            #pragma unroll
            for (int o = 2; o < 32; o <<= 1) cs[j] += __shfl_xor_sync(~0u, cs[j], o);
        }
        float* part = (float*)(smem + K1_OFF_PART);
        if (lane < 2) {
            #pragma unroll
            for (int j = 0; j < 8; j++) part[hw * 16 + lane * 8 + j] = cs[j];
        }
        named_bar<2, 96>();
        const int ht = tid - 288;
        if (ht < 16 && b < 120) st_tagged(&g_colsum[b * 16 + ht], part[ht] + part[16 + ht] + part[32 + ht], tag);
        if (tid == 288) TL(0, 9);
        float* scs = (float*)(smem + K1_OFF_CS);
        float2* srs = (float2*)(smem + K1_OFF_RS);
        {
            const bool hr = ht < 32, hc = ht < 24;
            uint4 r0, r1, c0, c1;
            int it = 0;
            bool ok;
            do {
                r0 = ld_tagged2(&g_rowstat[mt * 128 + ht]);
                c0 = ld_tagged2(&g_colsum[nt * 240 + 2 * ht]);
                r1 = hr ? ld_tagged2(&g_rowstat[mt * 128 + 96 + ht]) : r0;
                c1 = hc ? ld_tagged2(&g_colsum[nt * 240 + 192 + 2 * ht]) : c0;
                ok = r0.y == tag && r0.w == tag && c0.y == tag && c0.w == tag && r1.y == tag && r1.w == tag && c1.y == tag && c1.w == tag;
                if (++it > (1 << 22)) __trap();
            } while (!ok);
            srs[ht] = make_float2(__uint_as_float(r0.x), __uint_as_float(r0.z));
            *(float2*)(scs + 2 * ht) = make_float2(__uint_as_float(c0.x), __uint_as_float(c0.z));
            if (hr) srs[96 + ht] = make_float2(__uint_as_float(r1.x), __uint_as_float(r1.z));
            if (hc) *(float2*)(scs + 192 + 2 * ht) = make_float2(__uint_as_float(c1.x), __uint_as_float(c1.z));
        }
        __syncwarp();
        if (lane == 0) mbar_arrive(barStat);
        if (ht == 0) TL(0, 5);
        uint4 wt[2][4];
        #pragma unroll
        for (int i = 0; i < 2; i++) {
            const int item = b * 100 + ht + 96 * i, k = ((item >> 3) / 20) * 8 + (item & 7), grp = (item >> 3) % 20;
            if (i == 0 || ht < 4) {
                #pragma unroll
                for (int c = 0; c < 4; c++) wt[i][c] = ldg_v4(wo + (size_t)k * D_ + grp * 32 + c * 8);
            }
        }
        #pragma unroll
        for (int i = 0; i < 2; i++) {
            const int item = b * 100 + ht + 96 * i, k = ((item >> 3) / 20) * 8 + (item & 7), grp = (item >> 3) % 20;
            if (i == 0 || ht < 4) {
                uint8_t* dst = g_wo_img + ((grp / 5) * 10 + (k >> 6)) * 20480 + ((k >> 3) & 7) * 2560 + (grp % 5) * 512 + (k & 7) * 16;
                *(uint4*)(dst) = make_uint4(wt[i][0].x, wt[i][1].x, wt[i][2].x, wt[i][3].x);
                *(uint4*)(dst + 128) = make_uint4(wt[i][0].y, wt[i][1].y, wt[i][2].y, wt[i][3].y);
                *(uint4*)(dst + 256) = make_uint4(wt[i][0].z, wt[i][1].z, wt[i][2].z, wt[i][3].z);
                *(uint4*)(dst + 384) = make_uint4(wt[i][0].w, wt[i][1].w, wt[i][2].w, wt[i][3].w);
            }
        }
        cluster_wait();
        if (hw == 0) { k1_store_pair<1>(sb, nt, mt); k1_store_pair<5>(sb, nt, mt); }
        else if (hw == 1) k1_store_pair<2>(sb, nt, mt);
        else k1_store_pair<3>(sb, nt, mt);
        bulk_wait_read();
    } else {
        cluster_arrive();
        cluster_wait();
        const int wg = warp >> 2, w4 = warp & 3, g = lane >> 2, t = lane & 3;
        float acc[120];
        const uint32_t hiA = 64u | (1u << 30), hiB = 64u | (1u << 30);
        #pragma unroll 1
        for (int kt = 0; kt < 10; kt++) {
            const int s = kt & 3;
            const uint32_t st = sb + s * K1_STAGE;
            mbar_wait(barFull + 8 * s, (kt >> 2) & 1);
            if (tid == 0 && kt == 0) TL(0, 1);
            if (tid == 0) TL(0, 10 + kt);
            const uint32_t sa = (st & 0x3FFFF) >> 4;
            const uint32_t loA = sa + wg * 512 + (1u << 16), loB = sa + 1024 + (512u << 16);
            wg_fence();
            #pragma unroll
            for (int kk = 0; kk < 4; kk++)
                mma_n240_ss(acc, make_desc(loA + 2 * kk, hiA), make_desc(loB + 128 * kk, hiB), (kt | kk) != 0);
            wg_commit();
            if (kt > 0) {
                wg_wait<1>();
                if (kt <= 6 && (tid & 127) == 0) {
                    const uint32_t eb = barEmpty + 8 * ((kt - 1) & 3);
                    mbar_arrive_cluster(eb, 0);
                    mbar_arrive_cluster(eb, 1);
                }
            }
        }
        wg_wait<0>();
        #pragma unroll
        for (int i = 0; i < 120; i++) asm volatile("" : "+f"(acc[i]) :: "memory");
        if (tid == 0) TL(0, 2);
        mbar_wait(barStat, 0);
        if (tid == 0) TL(0, 3);
        named_bar<1, 256>();

        const float* scs = (const float*)(smem + K1_OFF_CS);
        const float2* srs = (const float2*)(smem + K1_OFF_RS);
        const int r0 = wg * 64 + w4 * 16 + g;
        const float2 st0 = srs[r0], st1 = srs[r0 + 8];
        const int grp0 = wg * 8 + w4 * 2;
        const bool poly0 = (POLYMASK >> grp0) & 1, poly1 = (POLYMASK >> (grp0 + 1)) & 1;
        const int mi = lane >> 3, mr = lane & 7;
        const uint32_t aMain = sb + (grp0 + (mi & 1)) * 384 + (mi >> 1) * 128 + mr * 16;
        const uint32_t aC2 = sb + (grp0 + (mi & 1)) * 384 + 256 + (mi >> 1) * 6144 + mr * 16;
        const uint32_t kx0 = (t & 1) ? (poly0 ? KAUX1 : 0u) : (poly0 ? KAUX0 : 0x3F80u), kx1 = (t & 1) ? (poly1 ? KAUX1 : 0u) : (poly1 ? KAUX0 : 0x3F80u);
        const uint32_t vx0 = (t & 1) ? 0u : (poly0 ? 0xBF80u : 0x3F80u), vx1 = (t & 1) ? 0u : (poly1 ? 0xBF80u : 0x3F80u);
        #define K1_PAIR(P) do { \
            const int G = nt * 12 + 2 * P, type = G >> 5; \
            float ra = st0.y, rb = st1.y; \
            uint32_t x0 = 0, x1 = 0; \
            if (type == 0) { ra *= QSCALE; rb *= QSCALE; } \
            if (type == 1) { x0 = kx0; x1 = kx1; } \
            if (type == 2) { if (poly0) ra = -ra; if (poly1) rb = -rb; x0 = vx0; x1 = vx1; } \
            const float ma = -st0.x * ra, mb = -st1.x * rb; \
            float v[5][4]; \
            uint32_t r[5][2]; \
            _Pragma("unroll") \
            for (int jm = 0; jm < 5; jm++) { \
                const int j = P * 5 + jm; \
                const float2 c = *(const float2*)(scs + 8 * j + 2 * t); \
                v[jm][0] = fmaf(acc[4 * j], ra, c.x * ma); v[jm][1] = fmaf(acc[4 * j + 1], ra, c.y * ma); \
                v[jm][2] = fmaf(acc[4 * j + 2], rb, c.x * mb); v[jm][3] = fmaf(acc[4 * j + 3], rb, c.y * mb); \
                r[jm][0] = pack_bf(v[jm][0], v[jm][1]); r[jm][1] = pack_bf(v[jm][2], v[jm][3]); \
            } \
            stmatrix_x4(aMain + P * 12288, r[0][0], r[0][1], r[1][0], r[1][1]); \
            stmatrix_x4(aMain + P * 12288 + 6144, r[3][0], r[3][1], r[4][0], r[4][1]); \
            stmatrix_x4(aC2 + P * 12288, t < 2 ? r[2][0] : x0, t < 2 ? r[2][1] : x1, t < 2 ? x0 : r[2][0], t < 2 ? x1 : r[2][1]); \
            fence_async_smem(); \
            named_arrive<5 + P, 288>(); \
            if (type == 1) { \
                float nA0, nA1, nB0, nB1; \
                nA0 = fmaf(v[0][0], v[0][0], fmaf(v[0][1], v[0][1], fmaf(v[1][0], v[1][0], v[1][1] * v[1][1]))); \
                nA1 = fmaf(v[0][2], v[0][2], fmaf(v[0][3], v[0][3], fmaf(v[1][2], v[1][2], v[1][3] * v[1][3]))); \
                nB0 = fmaf(v[3][0], v[3][0], fmaf(v[3][1], v[3][1], fmaf(v[4][0], v[4][0], v[4][1] * v[4][1]))); \
                nB1 = fmaf(v[3][2], v[3][2], fmaf(v[3][3], v[3][3], fmaf(v[4][2], v[4][2], v[4][3] * v[4][3]))); \
                const float q0 = fmaf(v[2][0], v[2][0], v[2][1] * v[2][1]), q1 = fmaf(v[2][2], v[2][2], v[2][3] * v[2][3]); \
                if (t < 2) { nA0 += q0; nA1 += q1; } else { nB0 += q0; nB1 += q1; } \
                nA0 += __shfl_xor_sync(~0u, nA0, 1); nA1 += __shfl_xor_sync(~0u, nA1, 1); \
                nB0 += __shfl_xor_sync(~0u, nB0, 1); nB1 += __shfl_xor_sync(~0u, nB1, 1); \
                nA0 += __shfl_xor_sync(~0u, nA0, 2); nA1 += __shfl_xor_sync(~0u, nA1, 2); \
                nB0 += __shfl_xor_sync(~0u, nB0, 2); nB1 += __shfl_xor_sync(~0u, nB1, 2); \
                  \
                const uint32_t mA = __reduce_max_sync(~0u, max(__float_as_uint(nA0), __float_as_uint(nA1))); \
                const uint32_t mB = __reduce_max_sync(~0u, max(__float_as_uint(nB0), __float_as_uint(nB1))); \
                if (lane == 0) { \
                    const int h = G & 31; \
                    g_kmax[h * 128 + mt * 8 + warp] = __uint_as_float(mA); \
                    g_kmax[(h + 1) * 128 + mt * 8 + warp] = __uint_as_float(mB); \
                } \
            } \
        } while (0)
        K1_PAIR(0); K1_PAIR(1); K1_PAIR(2); K1_PAIR(3); K1_PAIR(4); K1_PAIR(5);
        #undef K1_PAIR
        if (tid == 0) TL(0, 4);
    }
}

#define K2_FIRST 2
constexpr int K2_OFF_BAR = 2 * HEAD_BYTES;
constexpr int K2_OFF_STG = K2_OFF_BAR + 256;
constexpr int K2_SMEM = K2_OFF_STG + 24576;

__device__ __forceinline__ float ex2(float y) { float e; asm("ex2.approx.ftz.f32 %0, %1;" : "=f"(e) : "f"(y)); return e; }
__device__ __forceinline__ uint32_t exp_pair_mufu(float y0, float y1) { return pack_bf(ex2(y0), ex2(y1)); }
__device__ __forceinline__ uint32_t hfma2(uint32_t a, uint32_t b, uint32_t c) {
    uint32_t r; asm("fma.rn.bf16x2 %0, %1, %2, %3;" : "=r"(r) : "r"(a), "r"(b), "r"(c)); return r;
}
__device__ __forceinline__ uint32_t exp_pair_poly(float y0, float y1, uint32_t cm, uint32_t ce) {
    const uint32_t G = __byte_perm(__float_as_uint(y0), __float_as_uint(y1), 0x6521);
    uint32_t w, z;
    asm("lop3.b32 %0, %1, %2, 0x3F003F00, 0xEA;" : "=r"(w) : "r"(G), "r"(cm));
    asm("lop3.b32 %0, %1, %2, 0x00030003, 0xEA;" : "=r"(z) : "r"(G), "r"(ce));
    return hfma2(G, w, z);
}
template<int MASK8>
__device__ __forceinline__ void softmax8(float (&s)[32], uint32_t (&p)[16], uint32_t cm, uint32_t ce) {
    #pragma unroll
    for (int i = 0; i < 32; i++) asm volatile("" : "+f"(s[i]) :: "memory");
    #pragma unroll
    for (int gi = 0; gi < 8; gi++) {
        if ((MASK8 >> gi) & 1) {
            p[2 * gi] = exp_pair_poly(s[4 * gi], s[4 * gi + 1], cm, ce);
            p[2 * gi + 1] = exp_pair_poly(s[4 * gi + 2], s[4 * gi + 3], cm, ce);
        } else {
            p[2 * gi] = exp_pair_mufu(s[4 * gi], s[4 * gi + 1]);
            p[2 * gi + 1] = exp_pair_mufu(s[4 * gi + 2], s[4 * gi + 3]);
        }
    }
}
__device__ __forceinline__ void attn_store(float (&o)[12], int row0, int head, int lane) {
    const int t = lane & 3, odd = head & 1;
    const int src = (lane & ~3) | (odd ? 0 : 2);
    const float l0 = __shfl_sync(~0u, o[8], src), l1 = __shfl_sync(~0u, o[10], src);
    const float r0 = __fdividef(1.f, l0), r1 = __fdividef(1.f, l1);
    bf16* o0 = g_o + (size_t)row0 * D_ + head * 20 + 2 * t;
    bf16* o1 = o0 + 8 * D_;
    const int c0 = odd ? 4 : 0, c2 = odd ? -4 : 16;
    *(uint32_t*)(o0 + c0) = pack_bf(o[0] * r0, o[1] * r0);
    *(uint32_t*)(o1 + c0) = pack_bf(o[2] * r1, o[3] * r1);
    *(uint32_t*)(o0 + c0 + 8) = pack_bf(o[4] * r0, o[5] * r0);
    *(uint32_t*)(o1 + c0 + 8) = pack_bf(o[6] * r1, o[7] * r1);
    if ((t < 2) != (bool)odd) {
        *(uint32_t*)(o0 + c2) = pack_bf(o[8] * r0, o[9] * r0);
        *(uint32_t*)(o1 + c2) = pack_bf(o[10] * r1, o[11] * r1);
    }
}

__device__ __forceinline__ void load_q(uint32_t sQ, int mt, uint32_t (&q)[6]) {
    const int lane = threadIdx.x & 31;
    const uint32_t base = sQ + ((threadIdx.x >> 7) * 16 + mt * 8 + ((threadIdx.x >> 5) & 3) * 2 + ((lane >> 3) & 1)) * 384 + (lane & 7) * 16;
    asm volatile("ldmatrix.sync.aligned.m8n8.x4.shared.b16 {%0,%1,%2,%3}, [%4];" : "=r"(q[0]), "=r"(q[1]), "=r"(q[2]), "=r"(q[3]) : "r"(base + (lane >> 4) * 128) : "memory");
    asm volatile("ldmatrix.sync.aligned.m8n8.x2.shared.b16 {%0,%1}, [%2];" : "=r"(q[4]), "=r"(q[5]) : "r"(base + 256) : "memory");
}
__device__ __forceinline__ uint32_t patch_q(uint32_t (&q)[6], float km2, bool isaux, int t) {
    uint32_t unsafe = 0;
    #pragma unroll
    for (int r = 0; r < 2; r++) {
        float n2 = 0;
        #pragma unroll
        for (int i = 0; i < 3; i++) {
            const float lo = bf_lo(q[2 * i + r]), hi = bf_hi(q[2 * i + r]);
            n2 = fmaf(lo, lo, fmaf(hi, hi, n2));
        }
        n2 += __shfl_xor_sync(~0u, n2, 1);
        n2 += __shfl_xor_sync(~0u, n2, 2);
        float rt; asm("sqrt.approx.f32 %0, %1;" : "=f"(rt) : "f"(n2 * km2));
        const float B = rt * 1.01f + 0.01f;
        unsafe |= !(B <= 47.25f);
        const uint32_t nb = ((__float_as_uint(B) + 0xffffu) >> 16) | 0x8000u;
        if (isaux) q[4 + r] = (t & 1) ? 0x3F803F80u : (nb | 0x3F800000u);
    }
    return unsafe;
}
__device__ __forceinline__ uint32_t cta_any(uint32_t v) {
    asm volatile("{\n.reg .pred p, q;\nsetp.ne.u32 q, %0, 0;\nbar.red.or.pred p, 1, 512, q;\nselp.u32 %0, 1, 0, p;\n}\n" : "+r"(v) :: "memory");
    return v;
}
__device__ __forceinline__ void attn_safe(uint32_t sK, uint32_t sV, uint32_t sBar, const uint32_t (&q0)[6], int rowbase, int head) {
    const int tid = threadIdx.x, lane = tid & 31, t = lane & 3;
    const bool isaux = (t < 2) == (bool)(head & 1);
    for (int j = 0; j < 9; j++) mbar_wait(sBar + j * 8, 0);
    uint32_t q1[6];
    load_q(sK + K2_OFF_STG, 1, q1);
    #pragma unroll 1
    for (int mt = 0; mt < 2; mt++) {
        uint4 qa = mt ? make_uint4(q1[0], q1[1], q1[2], q1[3]) : make_uint4(q0[0], q0[1], q0[2], q0[3]);
        uint4 qb = mt ? make_uint4(q1[4], q1[5], 0, 0) : make_uint4(q0[4], q0[5], 0, 0);
        if (isaux) { qb.x = 0; qb.y = 0; }
        float o[12], s[32];
        uint32_t p[16];
        #pragma unroll
        for (int i = 0; i < 12; i++) { o[i] = 0.f; asm volatile("" : "+f"(o[i]) :: "memory"); }
        float m0 = -INFINITY, m1 = -INFINITY;
        #pragma unroll 1
        for (int u = 0; u < 32; u++) {
            const uint32_t kb = (((sK + u * 3072) & 0x3FFFF) >> 4) + (8u << 16), vb = (((sV + u * 3072) & 0x3FFFF) >> 4) + (24u << 16);
            wg_fence();
            mma_n64_rs<0>(s, qa.x, qa.y, qa.z, qa.w, make_desc(kb, 24));
            mma_n64_rs<1>(s, qb.x, qb.y, qb.z, qb.w, make_desc(kb + 16, 24));
            wg_commit();
            wg_wait<0>();
            #pragma unroll
            for (int i = 0; i < 32; i++) asm volatile("" : "+f"(s[i]) :: "memory");
            float n0 = m0, n1 = m1;
            #pragma unroll
            for (int gi = 0; gi < 8; gi++) {
                n0 = fmaxf(n0, fmaxf(s[4 * gi], s[4 * gi + 1]));
                n1 = fmaxf(n1, fmaxf(s[4 * gi + 2], s[4 * gi + 3]));
            }
            n0 = fmaxf(n0, __shfl_xor_sync(~0u, n0, 1)); n0 = fmaxf(n0, __shfl_xor_sync(~0u, n0, 2));
            n1 = fmaxf(n1, __shfl_xor_sync(~0u, n1, 1)); n1 = fmaxf(n1, __shfl_xor_sync(~0u, n1, 2));
            const float a0 = ex2(m0 - n0), a1 = ex2(m1 - n1);
            m0 = n0; m1 = n1;
            #pragma unroll
            for (int c = 0; c < 3; c++) { o[4 * c] *= a0; o[4 * c + 1] *= a0; o[4 * c + 2] *= a1; o[4 * c + 3] *= a1; }
            const uint32_t mask8 = (POLYMASK >> ((u & 1) * 8)) & 0xFF;
            #pragma unroll
            for (int gi = 0; gi < 8; gi++) {
                const uint32_t sg = ((mask8 >> gi) & 1) ? 0x80008000u : 0u;
                p[2 * gi] = pack_bf(ex2(s[4 * gi] - m0), ex2(s[4 * gi + 1] - m0)) ^ sg;
                p[2 * gi + 1] = pack_bf(ex2(s[4 * gi + 2] - m1), ex2(s[4 * gi + 3] - m1)) ^ sg;
            }
            #pragma unroll
            for (int i = 0; i < 12; i++) asm volatile("" : "+f"(o[i]) :: "memory");
            wg_fence();
            mma_n24_rs<1>(o, p[0], p[1], p[2], p[3], make_desc(vb, 8));
            mma_n24_rs<1>(o, p[4], p[5], p[6], p[7], make_desc(vb + 48, 8));
            mma_n24_rs<1>(o, p[8], p[9], p[10], p[11], make_desc(vb + 96, 8));
            mma_n24_rs<1>(o, p[12], p[13], p[14], p[15], make_desc(vb + 144, 8));
            wg_commit();
            wg_wait<0>();
            #pragma unroll
            for (int i = 0; i < 12; i++) asm volatile("" : "+f"(o[i]) :: "memory");
        }
        attn_store(o, rowbase + mt * 64, head, lane);
    }
}

constexpr int K2_MOVERS = 4;
constexpr int WIMG_DOWN = 96 * 40960;
__device__ __forceinline__ void k2_mover(const CUtensorMap* tmG, const CUtensorMap* tmU, const CUtensorMap* tmD, uint32_t sb) {
    const int tid = threadIdx.x, warp = tid >> 5, lane = tid & 31;
    constexpr int NS = 6, NQ = 3;
    const uint32_t sOut = sb + NS * 24576, barFull = sOut + NQ * 24576, barEmpty = barFull + 8 * NS, barOut = barEmpty + 8 * NS, barFree = barOut + 8 * NQ;
    constexpr int NI = (192 + 80) / K2_MOVERS;
    if (tid == 0) {
        TL(4, 5);
        for (int i = 0; i < NS; i++) { mbar_init(barFull + 8 * i, 1); mbar_init(barEmpty + 8 * i, 12); }
        for (int i = 0; i < NQ; i++) { mbar_init(barOut + 8 * i, 12); mbar_init(barFree + 8 * i, 1); }
        fence_mbar_init();
        fence_async_smem();
    }
    __syncthreads();
    if (warp == 0) {
        if (lane == 0) {
            uint64_t pol;
            asm volatile("createpolicy.fractional.L2::evict_first.b64 %0, 1.0;" : "=l"(pol));
            int s = 0, ph = 1;
            #pragma unroll 1
            for (int n = 0; n < NI; n++) {
                const int id = n * K2_MOVERS + blockIdx.x;
                if (n >= NS) mbar_wait(barEmpty + 8 * s, ph);
                const bool gu = id < 192;
                const CUtensorMap* tm = gu ? (id < 96 ? tmG : tmU) : tmD;
                const int c0 = gu ? ((id % 96) >> 2) * 64 : ((id - 192) >> 3) * 64, c1 = gu ? (id & 3) * 160 : (id & 7) * 192;
                mbar_expect_tx(barFull + 8 * s, gu ? 20480 : 24576);
                asm volatile("cp.async.bulk.tensor.2d.shared::cluster.global.mbarrier::complete_tx::bytes.L2::cache_hint [%0], [%1, {%3, %4}], [%2], %5;"
                    :: "r"(sb + s * 24576), "l"(tm), "r"(barFull + 8 * s), "r"(c0), "r"(c1), "l"(pol) : "memory");
                if (++s == NS) { s = 0; ph ^= 1; }
            }
        }
    } else if (warp == 13) {
        if (lane == 0) {
            int q = 0, ph = 0;
            #pragma unroll 1
            for (int n = 0; n < NI; n++) {
                const int id = n * K2_MOVERS + blockIdx.x;
                const bool gu = id < 192;
                const int u = gu ? (id >= 96 ? id - 96 : id) : id - 192;
                const uint32_t len = gu ? 5120 : 6144;
                uint8_t* dst = g_wimg + (gu ? ((u >> 2) * 32 + (id >= 96 ? 4 : 0) + (u & 3)) * 5120 : WIMG_DOWN + ((u >> 3) * 32 + (u & 7)) * 6144);
                mbar_wait(barOut + 8 * q, ph);
                for (int bl = 0; bl < 4; bl++) bulk_s2g(dst + bl * 8 * len, sOut + q * 24576 + bl * 6144, len);
                bulk_commit();
                asm volatile("cp.async.bulk.wait_group.read 1;" ::: "memory");
                if (n > 0) mbar_arrive(barFree + 8 * (q == 0 ? NQ - 1 : q - 1));
                if (++q == NQ) { q = 0; ph ^= 1; }
            }
            bulk_wait_all();
            TL(4, 6);
        }
    } else if (warp <= 12) {
        const int g = lane >> 2, t = lane & 3, i = warp - 1;
        const int row = (i >> 1) * 32 + (((g >> 1) & 1) * 4 + t) * 2 + (g >> 2) * 16 + (i & 1);
        const uint32_t src = sb + row * 128, sw = (row & 7) ^ (g & 1), dst = sOut + i * 512 + lane * 16;
        int s = 0, ph = 0, q = 0, qh = 1;
        #pragma unroll 1
        for (int n = 0; n < NI; n++) {
            const bool on = n * K2_MOVERS + blockIdx.x >= 192 || i < 10;
            mbar_wait(barFull + 8 * s, ph);
            uint4 v[4];
            if (on) {
                #pragma unroll
                for (int bl = 0; bl < 4; bl++) v[bl] = lds_v4(src + s * 24576 + (((bl * 2) ^ sw) << 4));
            }
            if (n >= NQ) mbar_wait(barFree + 8 * q, qh);
            if (on) {
                #pragma unroll
                for (int bl = 0; bl < 4; bl++) sts_v4(dst + q * 24576 + bl * 6144, v[bl]);
            }
            fence_async_smem();
            __syncwarp();
            if (lane == 0) { mbar_arrive(barEmpty + 8 * s); mbar_arrive(barOut + 8 * q); }
            if (++s == NS) { s = 0; ph ^= 1; }
            if (++q == NQ) { q = 0; qh ^= 1; }
        }
    }
}

static_assert((POLYMASK & 0xFF) == (POLYMASK >> 8), "both 64-key tiles of a 128-key block use the same pattern");

__global__ void __launch_bounds__(512, 1)
k2_attn(const __grid_constant__ CUtensorMap tmG, const __grid_constant__ CUtensorMap tmU, const __grid_constant__ CUtensorMap tmD,
        uint32_t cm, uint32_t ce) {
    extern __shared__ __align__(1024) uint8_t smem[];
    if (blockIdx.x < K2_MOVERS) {
        k2_mover(&tmG, &tmU, &tmD, smem_u32(smem));
        return;
    }
    const int bid = blockIdx.x - K2_MOVERS;
    const int head = bid >> 2, quarter = bid & 3;
    const uint32_t sK = smem_u32(smem), sV = sK + HEAD_BYTES, sBar = sK + K2_OFF_BAR, sStg = sK + K2_OFF_STG;
    const int tid = threadIdx.x, wg = tid >> 7, warp = (tid >> 5) & 3, lane = tid & 31, g = lane >> 2, t = lane & 3;
    if (tid == 0) TL(1, 0);
    if (tid == 0) {
        for (int i = 0; i < 9; i++) mbar_init(sBar + i * 8, 1);
        fence_mbar_init();
        fence_async_smem();
        for (int i = 0; i < 4; i++) mbar_expect_tx(sBar + i * 8, 12288);
        mbar_expect_tx(sBar + 32, 4 * 12288);
        mbar_expect_tx(sBar + 40, 12288);
        mbar_expect_tx(sBar + 48, 12288);
        mbar_expect_tx(sBar + 56, 4 * 12288);
        mbar_expect_tx(sBar + 64, 4 * 12288);
    }
    if (tid >= 64 && tid < 64 + 148) *(uint4*)(g_xc + (bid * 148 + tid - 64) * 16) = make_uint4(~0u, ~0u, ~0u, ~0u);
    __syncthreads();
    pdl_wait();
    pdl_launch();
    if (tid == 0) TL(1, 1);
    const uint8_t* Qp = g_qkv + (size_t)head * HEAD_BYTES + (quarter * 64 + wg * 16) * 384;
    const uint8_t* Kp = g_qkv + (size_t)(32 + head) * HEAD_BYTES;
    const uint8_t* Vp = g_qkv + (size_t)(64 + head) * HEAD_BYTES;
    if ((tid & 127) == 0) {
        bulk_g2s(sStg + wg * 6144, Qp, 3072, sBar + 40);
        if (wg < K2_FIRST) {
            bulk_g2s(sK + wg * 6144, Kp + wg * 6144, 6144, sBar + wg * 8);
            bulk_g2s(sV + wg * 6144, Vp + wg * 6144, 6144, sBar + wg * 8);
        }
    }
    const float4 k4 = __ldcg((const float4*)(g_kmax + head * 128) + lane);
    float km2;
    {
        const uint32_t m = max(max(__float_as_uint(k4.x), __float_as_uint(k4.y)), max(__float_as_uint(k4.z), __float_as_uint(k4.w)));
        km2 = __uint_as_float(__reduce_max_sync(~0u, m));
    }
    const int rowbase = quarter * 512 + wg * 128 + warp * 16 + g;
    const bool isaux = (t < 2) == (bool)(head & 1);
    uint32_t q0[6], q1[6];
    mbar_wait(sBar + 40, 0);
    if (tid == 0) TL(1, 17);
    if (tid == 384) {
        for (int c = K2_FIRST; c < 4; c++) {
            bulk_g2s(sK + c * 6144, Kp + c * 6144, 6144, sBar + c * 8);
            bulk_g2s(sV + c * 6144, Vp + c * 6144, 6144, sBar + c * 8);
        }
        for (int c = 0; c < 3; c++) {
            const uint32_t bar = sBar + (c == 0 ? 32 : 48 + 8 * c);
            bulk_g2s(sK + (4 + 4 * c) * 6144, Kp + (4 + 4 * c) * 6144, 4 * 6144, bar);
            bulk_g2s(sV + (4 + 4 * c) * 6144, Vp + (4 + 4 * c) * 6144, 4 * 6144, bar);
            if (c == 0) bulk_g2s(sStg + 3 * 6144 + 3072, Qp + 3072, 3072, sBar + 48);
        }
    } else if ((tid & 127) == 0) {
        bulk_g2s(sStg + wg * 6144 + 3072, Qp + 3072, 3072, sBar + 48);
    }
    load_q(sStg, 0, q0);
    uint32_t unsafe = patch_q(q0, km2, isaux, t);
    unsafe = cta_any(unsafe);
    if (tid == 0) TL(1, 16);

    float s[32];
    float o[12];
    uint32_t p[16];
    uint4 qa = make_uint4(q0[0], q0[1], q0[2], q0[3]), qb = make_uint4(q0[4], q0[5], 0, 0);
    uint64_t dk, dv;
    #define SET_DESC(KT, VT) do { uint32_t b_; asm volatile("mov.u32 %0, smem;" : "=r"(b_)); \
        dk = make_desc((b_ >> 4) + (KT) * 192 + (8u << 16), 24); dv = make_desc(((b_ + HEAD_BYTES) >> 4) + (VT) * 192 + (24u << 16), 8); } while (0)
    #define ISSUE_QK() do { mma_n64_rs<0>(s, qa.x, qa.y, qa.z, qa.w, dk); mma_n64_rs<1>(s, qb.x, qb.y, qb.z, qb.w, dk + 16); dk += 192; } while (0)
    #define PV(SD) do { mma_n24_rs<SD>(o, p[0], p[1], p[2], p[3], dv); mma_n24_rs<1>(o, p[4], p[5], p[6], p[7], dv + 48); \
                      mma_n24_rs<1>(o, p[8], p[9], p[10], p[11], dv + 96); mma_n24_rs<1>(o, p[12], p[13], p[14], p[15], dv + 144); dv += 192; } while (0)
    constexpr int MA = POLYMASK & 0xFF;
    #define STEP(SD) do { wg_wait<0>(); softmax8<MA>(s, p, cm, ce); wg_fence(); PV(SD); ISSUE_QK(); wg_commit(); } while (0)
    if (!__any_sync(~0u, unsafe)) {
        mbar_wait_warp(sBar, 0);
        if (tid == 0) { TL(1, 2); TLC(1, 5); }
        SET_DESC(0, 0);
        wg_fence();
        ISSUE_QK();
        wg_commit();
        STEP(0);
        SET_DESC(2, 1);
        #pragma unroll 1
        for (int j = 1; j < 7; j++) {
            if (j & 1) mbar_wait_warp(sBar + 4 + j * 4, 0);
            STEP(1);
        }
        if (tid == 0) TLC(1, 18);
        mbar_wait_warp(sBar + 48, 0);
        load_q(sStg, 1, q1);
        unsafe = cta_any(patch_q(q1, km2, isaux, t));
    }
    if (__any_sync(~0u, unsafe)) {
        wg_wait<0>();
        #pragma unroll
        for (int i = 0; i < 32; i++) asm volatile("" : "+f"(s[i]) :: "memory");
        #pragma unroll
        for (int i = 0; i < 12; i++) asm volatile("" : "+f"(o[i]) :: "memory");
        attn_safe(sK, sV, sBar, q0, rowbase, head);
        return;
    }
    #pragma unroll 1
    for (int c = 0; c < 3; c++) {
        mbar_wait_warp(sBar + (c == 0 ? 32 : 48 + 8 * c), 0);
        if (tid == 0 && c == 0) TLC(1, 19);
        SET_DESC(8 + 8 * c, 7 + 8 * c);
        #pragma unroll 1
        for (int j = 0; j < 8; j++) STEP(1);
    }
    wg_wait<0>();
    qa = make_uint4(q1[0], q1[1], q1[2], q1[3]); qb = make_uint4(q1[4], q1[5], 0, 0);
    softmax8<MA>(s, p, cm, ce);
    SET_DESC(0, 31);
    wg_fence();
    PV(1);
    ISSUE_QK();
    wg_commit();
    wg_wait<0>();
    #pragma unroll
    for (int i = 0; i < 12; i++) asm volatile("" : "+f"(o[i]) :: "memory");
    attn_store(o, rowbase, head, lane);
    if ((tid & 127) == 0) TL(1, 8 + wg);
    if (tid == 0) { TL(1, 3); TLC(1, 6); }
    SET_DESC(1, 0);
    STEP(0);
    SET_DESC(2, 1);
    #pragma unroll 1
    for (int j = 0; j < 30; j++) STEP(1);
    wg_wait<0>();
    softmax8<MA>(s, p, cm, ce);
    SET_DESC(0, 31);
    wg_fence();
    PV(1);
    wg_commit();
    wg_wait<0>();
    #pragma unroll
    for (int i = 0; i < 12; i++) asm volatile("" : "+f"(o[i]) :: "memory");
    attn_store(o, rowbase + 64, head, lane);
    if ((tid & 127) == 0) TL(1, 12 + wg);
    if (tid == 0) { TL(1, 4); TLC(1, 7); }
    #undef SET_DESC
    #undef STEP
    #undef PV
    #undef ISSUE_QK
}

#define K3_DRY_E 0
#define K3_DRY_T 0
#define K3_WKT 10
#define K3_NPRE 3
constexpr int K3_NB = 7;
constexpr int K3_BT = 20480;
constexpr int K3_OFF_B = 10 * 8192;
constexpr int K3_OFF_BAR = K3_OFF_B + K3_NB * K3_BT;
constexpr int K3_OFF_TOP = K3_OFF_BAR + 128;
constexpr int K3_OFF_SEL = K3_OFF_TOP + 256;
constexpr int K3_OFF_RED = K3_OFF_SEL + 16;
constexpr int K3_OFF_HL = K3_OFF_RED + 1024;
constexpr int K3_XS = 1344, K3_HS = 3136;
constexpr int K3_OFF_X = K3_OFF_HL + 128;
constexpr int K3_SMEM = K3_OFF_X + 2 * K3_XS;
constexpr int K3_OFF_WG = K3_OFF_B + 3 * K3_BT, K3_OFF_WD = 0, K3_OFF_HF = 6 * 8192;

__device__ __forceinline__ uint32_t order_key(float v) {
    const uint32_t u = __float_as_uint(v);
    return u ^ (((int)u >> 31) | 0x80000000u);
}
__device__ __forceinline__ float key_value(uint32_t k) { return __uint_as_float(k ^ ((~(int)k >> 31) | 0x80000000u)); }
__device__ __forceinline__ void warp_top2(uint32_t& k0, uint32_t& i0, uint32_t& k1, uint32_t& i1) {
    const uint32_t m0 = __reduce_max_sync(~0u, k0);
    const uint32_t j0 = __reduce_min_sync(~0u, k0 == m0 ? i0 : 0xffffffffu);
    const bool won = i0 == j0;
    const uint32_t kk = won ? k1 : k0, ii = won ? i1 : i0;
    const uint32_t m1 = __reduce_max_sync(~0u, kk);
    const uint32_t j1 = __reduce_min_sync(~0u, kk == m1 ? ii : 0xffffffffu);
    k0 = m0; i0 = j0; k1 = m1; i1 = j1;
}
__device__ __forceinline__ uint4 ldx_v4(const void* p) {
    uint4 v; asm volatile("ld.relaxed.gpu.global.v4.b32 {%0,%1,%2,%3}, [%4];" : "=r"(v.x), "=r"(v.y), "=r"(v.z), "=r"(v.w) : "l"(p) : "memory"); return v;
}
__device__ __forceinline__ void stx_v4(void* p, uint32_t a, uint32_t b, uint32_t c, uint32_t d, bool on) {
    asm volatile("{\n.reg .pred p;\nsetp.ne.u32 p, %5, 0;\n@p st.relaxed.gpu.global.v4.b32 [%0], {%1,%2,%3,%4};\n}\n"
        :: "l"(p), "r"(a), "r"(b), "r"(c), "r"(d), "r"((uint32_t)on) : "memory");
}
__device__ __forceinline__ void st_v4(void* p, uint32_t a, uint32_t b, uint32_t c, uint32_t d, bool on) {
    asm volatile("{\n.reg .pred p;\nsetp.ne.u32 p, %5, 0;\n@p st.global.v4.b32 [%0], {%1,%2,%3,%4};\n}\n"
        :: "l"(p), "r"(a), "r"(b), "r"(c), "r"(d), "r"((uint32_t)on) : "memory");
}
__device__ __forceinline__ bool valid4(const uint4 v) { return v.x != ~0u && v.y != ~0u && v.z != ~0u && v.w != ~0u; }
__device__ __forceinline__ uint32_t hadd_bf2(uint32_t a, uint32_t b) {
    uint32_t r; asm("add.rn.bf16x2 %0, %1, %2;" : "=r"(r) : "r"(a), "r"(b)); return r;
}
template<int NB>
__device__ __forceinline__ void gemv16(const uint4 (&w)[2 * NB], uint32_t xs, uint32_t pitch, float* red, int lane) {
    const int g = lane >> 2, t = lane & 3;
    const uint32_t xa = xs + ((g >> 1) & 1) * pitch + ((g >> 2) * 4 + t) * 4;
    const uint32_t selLo = (g & 1) ? 0x1044u : 0x4410u, selHi = (g & 1) ? 0x3244u : 0x4432u;
    float c[4][4];
    #pragma unroll
    for (int j = 0; j < 4; j++) { c[j][0] = 0.f; c[j][1] = 0.f; c[j][2] = 0.f; c[j][3] = 0.f; }
    #pragma unroll
    for (int i = 0; i < NB; i++) {
        uint32_t x0, x1;
        asm volatile("ld.shared.b32 %0, [%1];" : "=r"(x0) : "r"(xa + 64 * i) : "memory");
        asm volatile("ld.shared.b32 %0, [%1];" : "=r"(x1) : "r"(xa + 64 * i + 32) : "memory");
        const uint32_t a0 = __byte_perm(x0, 0, selLo), a2 = __byte_perm(x0, 0, selHi), a1 = __byte_perm(x1, 0, selLo), a3 = __byte_perm(x1, 0, selHi);
        const uint32_t b0[4] = {w[2 * i].x, w[2 * i].y, w[2 * i].z, w[2 * i].w}, b1[4] = {w[2 * i + 1].x, w[2 * i + 1].y, w[2 * i + 1].z, w[2 * i + 1].w};
        #pragma unroll
        for (int j = 0; j < 4; j++)
            asm volatile("mma.sync.aligned.m16n8k16.row.col.f32.bf16.bf16.f32 {%0,%1,%2,%3}, {%4,%5,%6,%7}, {%8,%9}, {%0,%1,%2,%3};"
                : "+f"(c[j][0]), "+f"(c[j][1]), "+f"(c[j][2]), "+f"(c[j][3]) : "r"(a0), "r"(a1), "r"(a2), "r"(a3), "r"(b0[j]), "r"(b1[j]));
    }
    float v[4];
    #pragma unroll
    for (int j = 0; j < 4; j++) {
        const float keep = t < 2 ? c[j][0] : c[j][3], send = t < 2 ? c[j][1] : c[j][2];
        v[j] = keep + __shfl_xor_sync(~0u, send, 2);
    }
    const bool odd = t & 1;
    const float e0 = (odd ? v[2] : v[0]) + __shfl_xor_sync(~0u, odd ? v[0] : v[2], 17);
    const float e1 = (odd ? v[3] : v[1]) + __shfl_xor_sync(~0u, odd ? v[1] : v[3], 17);
    if ((t & 1) == (g >> 2)) {
        float* r = red + ((g >> 1) & 1) * 16 + (t >> 1) * 8 + (t & 1) * 4 + (g & 1);
        r[0] = e0; r[2] = e1;
    }
}

__global__ void __launch_bounds__(384, 1)
k3_tail(const __grid_constant__ CUtensorMap tmO, const bf16* __restrict__ x, const bf16* __restrict__ wr, const bf16* __restrict__ wgate,
        bf16* __restrict__ out) {
    extern __shared__ __align__(1024) uint8_t smem[];
    const uint32_t sb = smem_u32(smem);
    uint32_t barFull = sb + K3_OFF_BAR;
    const int tid = threadIdx.x, warp = tid >> 5, lane = tid & 31, b = blockIdx.x;
    const int nt = b & 3, mt = b >> 2;
    const int g = lane >> 2, t = lane & 3;
    const uint8_t* dummy = (const uint8_t*)wgate + b * 4096;
    float acc[80], wv[40], wsum;
    if (warp < 4) {
        cluster_arrive();
        const uint32_t hiA = 64u | (1u << 30), hiB = 8u;
        const uint32_t sa = __reduce_max_sync(~0u, (sb & 0x3FFFF) >> 4);
        uint4 xa[5], xb[5], wp[5];
        const bf16* x0 = x + (size_t)(mt * 64 + warp * 16 + g) * D_ + nt * 160 + 8 * t;
        #pragma unroll
        for (int J = 0; J < 5; J++) { xa[J] = ldg_v4(x0 + 32 * J); xb[J] = ldg_v4(x0 + 8 * D_ + 32 * J); wp[J] = ldg_v4(wr + nt * 160 + 8 * t + 32 * J); }
        if (tid == 0) TL(2, 7);
        cluster_wait();
        wsum = 0.f;
        #pragma unroll
        for (int J = 0; J < 5; J++) {
            const uint32_t xw0[4] = {xa[J].x, xa[J].y, xa[J].z, xa[J].w}, xw1[4] = {xb[J].x, xb[J].y, xb[J].z, xb[J].w};
            const uint32_t ww[4] = {wp[J].x, wp[J].y, wp[J].z, wp[J].w};
            #pragma unroll
            for (int jj = 0; jj < 4; jj++) {
                const int j = 4 * J + jj;
                acc[4 * j] = bf_lo(xw0[jj]); acc[4 * j + 1] = bf_hi(xw0[jj]); acc[4 * j + 2] = bf_lo(xw1[jj]); acc[4 * j + 3] = bf_hi(xw1[jj]);
                wv[2 * j] = bf_lo(ww[jj]); wv[2 * j + 1] = bf_hi(ww[jj]);
                wsum += wv[2 * j] + wv[2 * j + 1];
            }
        }
        wsum += __shfl_xor_sync(~0u, wsum, 1);
        wsum += __shfl_xor_sync(~0u, wsum, 2);
        asm volatile("" : "+f"(wsum));
        #pragma unroll
        for (int i = 0; i < 40; i++) asm volatile("" : "+f"(wv[i]));
        #pragma unroll
        for (int i = 0; i < 80; i++) asm volatile("" : "+f"(acc[i]) :: "memory");
        asm volatile("" : "+r"(barFull));
        named_arrive<5, 352>();
        pdl_wait();
        #pragma unroll 1
        for (int kt = 0; kt < 10; kt++) {
            mbar_wait_warp(barFull + 8 * kt, 0);
            if (tid == 0 && kt == 0) TL(2, 2);
            const int slot = kt < K3_NB ? kt : kt - K3_NB;
            const uint32_t loA = sa + kt * 512 + (1u << 16), loB = sa + (K3_OFF_B >> 4) + slot * (K3_BT >> 4) + (160u << 16);
            wg_fence();
            #pragma unroll
            for (int kk = 0; kk < 4; kk++)
                mma_n160_ss(acc, make_desc(loA + 2 * kk, hiA), make_desc(loB + 320 * kk, hiB), 1);
            wg_commit();
            if (((0xE | (K3_WKT < 10 ? 1 << (K3_WKT - 1) : 0)) >> kt) & 1) {
                wg_wait<1>();
                if (lane == 0) mbar_arrive(barFull + 80 + 8 * min(kt - 1, 3));
            }
        }
        wg_wait<0>();
        if (K3_WKT == 10 && lane == 0) mbar_arrive(barFull + 104);
        #pragma unroll
        for (int i = 0; i < 80; i++) asm volatile("" : "+f"(acc[i]) :: "memory");
        if (tid == 0) { TL(2, 3); TLC(3, 16); }
    } else {
        if (warp == 11) {
            const uint8_t* img = g_wo_img + nt * (10 * K3_BT);
            const uint32_t barEmpty = barFull + 80;
            if (lane == 0) {
                TL(2, 0);
                tmap_prefetch(&tmO);
                for (int i = 0; i < 10; i++) mbar_init(barFull + 8 * i, 1);
                for (int i = 0; i < 4; i++) mbar_init(barEmpty + 8 * i, 4);
                mbar_init(barFull + 112, 1);
                fence_mbar_init();
                fence_async_smem();
                for (int i = 0; i < 10; i++) mbar_expect_tx(barFull + 8 * i, 8192 + K3_BT);
                mbar_expect_tx(barFull + 112, (b < 96 ? 40960 : 0) + (b >= 88 ? 49152 : 0));
                for (int kt = 0; kt < K3_NPRE; kt++) bulk_g2s(sb + K3_OFF_B + kt * K3_BT, img + kt * K3_BT, K3_BT, barFull + 8 * kt);
            }
            __syncwarp();
            cluster_arrive();
            cluster_wait();
            if (lane == 0) {
                uint32_t rank; asm("mov.u32 %0, %%cluster_ctarank;" : "=r"(rank));
                pdl_wait();
                TL(2, 1);
                #pragma unroll 1
                for (int kt = 0; kt < 10; kt++) {
                    if ((kt & 1) == (int)rank) tma_2d_mc(sb + kt * 8192, &tmO, kt * 64, mt * 64, barFull + 8 * kt, (uint16_t)3);
                    if (kt >= K3_NPRE && kt < K3_NB) bulk_g2s(sb + K3_OFF_B + kt * K3_BT, img + kt * K3_BT, K3_BT, barFull + 8 * kt);
                }
                #pragma unroll 1
                for (int j = 0; j < 10 - K3_NB; j++) {
                    mbar_wait(barEmpty + 8 * j, 0);
                    bulk_g2s(sb + K3_OFF_B + j * K3_BT, img + (K3_NB + j) * K3_BT, K3_BT, barFull + 8 * (K3_NB + j));
                }
                if (b == 0) g_epoch = g_epoch + 1;
                mbar_wait(barEmpty + 24, 0);
                TL(3, 0);
                if (b < 96) bulk_g2s(sb + K3_OFF_WG, g_wimg + b * 40960, 40960, barFull + 112);
                if (b >= 88) bulk_g2s(sb + K3_OFF_WD, g_wimg + WIMG_DOWN + (b - 88) * 49152, 49152, barFull + 112);
            }
            __syncwarp();
        } else {
            cluster_arrive();
            cluster_wait();
            named_bar<5, 352>();
        }
        #pragma unroll
        for (int i = 0; i < 80; i++) asm volatile("" : "=f"(acc[i]));
        #pragma unroll
        for (int i = 0; i < 40; i++) asm volatile("" : "=f"(wv[i]));
        asm volatile("" : "=f"(wsum));
    }
    uint32_t real_ = warp < 4;
    asm volatile("" : "+r"(real_));
    const bool real = __reduce_max_sync(~0u, real_);
    if (real || (K3_DRY_E && warp != 11)) {
        const int r0 = mt * 64 + (warp & 3) * 16 + g;
        float s0 = 0.f, q0 = 0.f, d0 = 0.f, s1 = 0.f, q1 = 0.f, d1 = 0.f;
        #pragma unroll
        for (int j = 0; j < 20; j++) {
            const float a0 = acc[4 * j], a1 = acc[4 * j + 1], b0 = acc[4 * j + 2], b1 = acc[4 * j + 3];
            s0 += a0 + a1; q0 = fmaf(a0, a0, fmaf(a1, a1, q0)); d0 = fmaf(a0, wv[2 * j], fmaf(a1, wv[2 * j + 1], d0));
            s1 += b0 + b1; q1 = fmaf(b0, b0, fmaf(b1, b1, q1)); d1 = fmaf(b0, wv[2 * j], fmaf(b1, wv[2 * j + 1], d1));
        }
        #pragma unroll
        for (int o = 1; o < 4; o <<= 1) {
            s0 += __shfl_xor_sync(~0u, s0, o); q0 += __shfl_xor_sync(~0u, q0, o); d0 += __shfl_xor_sync(~0u, d0, o);
            s1 += __shfl_xor_sync(~0u, s1, o); q1 += __shfl_xor_sync(~0u, q1, o); d1 += __shfl_xor_sync(~0u, d1, o);
        }
        uint8_t* part = g_xc + XC_PART + r0 * 64;
        stx_v4(part + (t & 1) * 512 + nt * 16, __float_as_uint(t & 1 ? s1 : s0), __float_as_uint(t & 1 ? q1 : q0), __float_as_uint(t & 1 ? d1 : d0),
               __float_as_uint(wsum), real && t < 2);
        if (tid == 0) { TL(2, 4); TLC(3, 17); }
        uint4 ua, ub;
        {
            const uint8_t* lp = real ? part + t * 16 : dummy + lane * 16;
            uint32_t it = 0;
            bool ok;
            do {
                ua = ldx_v4(lp); ub = ldx_v4(lp + 512);
                ok = valid4(ua) && valid4(ub);
                if (++it > (1u << 22)) __trap();
            } while (real && !__all_sync(~0u, ok));
        }
        if (tid == 0) { TL(2, 5); TLC(3, 18); }
        s0 = __uint_as_float(ua.x); q0 = __uint_as_float(ua.y); d0 = __uint_as_float(ua.z);
        s1 = __uint_as_float(ub.x); q1 = __uint_as_float(ub.y); d1 = __uint_as_float(ub.z);
        float ws = __uint_as_float(ua.w);
        #pragma unroll
        for (int o = 1; o < 4; o <<= 1) {
            s0 += __shfl_xor_sync(~0u, s0, o); q0 += __shfl_xor_sync(~0u, q0, o); d0 += __shfl_xor_sync(~0u, d0, o);
            s1 += __shfl_xor_sync(~0u, s1, o); q1 += __shfl_xor_sync(~0u, q1, o); d1 += __shfl_xor_sync(~0u, d1, o);
            ws += __shfl_xor_sync(~0u, ws, o);
        }
        const float mua = s0 * (1.f / D_), mub = s1 * (1.f / D_);
        const float rsa = rsqrtf(fmaxf(q0 * (1.f / D_) - mua * mua, 0.f) + 1e-5f), rsb = rsqrtf(fmaxf(q1 * (1.f / D_) - mub * mub, 0.f) + 1e-5f);
        uint32_t k0 = order_key(t == 0 ? rsa * (d0 - mua * ws) : rsb * (d1 - mub * ws)), i0 = r0 + 8 * t, k1, i1;
        if (t >= 2) { k0 = 0; i0 = ~0u; }
        k1 = 0; i1 = ~0u;
        if (tid == 0) TLC(3, 19);
        warp_top2(k0, i0, k1, i1);
        if (tid == 0) TLC(3, 20);
        uint4* s_top = (uint4*)(smem + K3_OFF_TOP);
        if (lane == 0) s_top[warp] = make_uint4(k0, i0, k1, i1);
        named_bar_rr(real ? 3 : 6, real ? 128 : 224);
        if (tid == 0) TLC(3, 21);
        {
            const uint4 v = s_top[(warp & 12) + t];
            k0 = v.x; i0 = v.y; k1 = v.z; i1 = v.w;
            warp_top2(k0, i0, k1, i1);
        }
        if (real && tid == 0) {
            asm volatile("st.relaxed.gpu.global.v2.b64 [%0], {%1, %2};" :: "l"(g_xc + XC_KEYS + nt * 512 + mt * 16),
                "l"(((unsigned long long)k0 << 32) | (2 * i0)), "l"(((unsigned long long)k1 << 32) | (2 * i1 + 1)) : "memory");
            TL(2, 9); TLC(3, 22);
        }
        const bool ca = real && (r0 == i0 || r0 == i1), cb = real && (r0 + 8 == i0 || r0 + 8 == i1);
        uint8_t* cpa = g_xc + XC_CAND + (mt * 2 + (r0 == i1)) * 2560 + (nt * 160 + 8 * t) * 2;
        uint8_t* cpb = g_xc + XC_CAND + (mt * 2 + (r0 + 8 == i1)) * 2560 + (nt * 160 + 8 * t) * 2;
        bf16* o0 = out + (size_t)r0 * D_ + nt * 160 + 8 * t;
        const float ma = -mua * rsa, mb = -mub * rsb;
        uint32_t oa[20], ob[20];
        #pragma unroll
        for (int J = 0; J < 5; J++) {
            uint32_t ha[4], hb[4], la[4], lb[4];
            #pragma unroll
            for (int jj = 0; jj < 4; jj++) {
                const int j = 4 * J + jj;
                ha[jj] = pack_bf(acc[4 * j], acc[4 * j + 1]); hb[jj] = pack_bf(acc[4 * j + 2], acc[4 * j + 3]);
                la[jj] = pack_bf(fmaf(acc[4 * j], rsa, ma), fmaf(acc[4 * j + 1], rsa, ma));
                lb[jj] = pack_bf(fmaf(acc[4 * j + 2], rsb, mb), fmaf(acc[4 * j + 3], rsb, mb));
                oa[j] = hadd_bf2(ha[jj], la[jj]); ob[j] = hadd_bf2(hb[jj], lb[jj]);
            }
            stx_v4(cpa + 64 * J, la[0], la[1], la[2], la[3], ca);
            stx_v4(cpb + 64 * J, lb[0], lb[1], lb[2], lb[3], cb);
            stx_v4(cpa + 64 * J + 1280, ha[0], ha[1], ha[2], ha[3], ca);
            stx_v4(cpb + 64 * J + 1280, hb[0], hb[1], hb[2], hb[3], cb);
            st_v4(o0 + 32 * J, oa[4 * J], oa[4 * J + 1], oa[4 * J + 2], oa[4 * J + 3], real && !ca);
            st_v4(o0 + 8 * D_ + 32 * J, ob[4 * J], ob[4 * J + 1], ob[4 * J + 2], ob[4 * J + 3], real && !cb);
        }
        if (real) {
            if (tid == 0) { TL(2, 8); TLC(3, 23); }
            named_bar<2, 160>();
            const uint2 sel = *(const uint2*)(smem + K3_OFF_SEL);
            const uint32_t row0 = sel.x >> 1, row1 = sel.y >> 1;
            const bool wa = ca && r0 != row0 && r0 != row1, wb = cb && r0 + 8 != row0 && r0 + 8 != row1;
            #pragma unroll
            for (int J = 0; J < 5; J++) {
                st_v4(o0 + 32 * J, oa[4 * J], oa[4 * J + 1], oa[4 * J + 2], oa[4 * J + 3], wa);
                st_v4(o0 + 8 * D_ + 32 * J, ob[4 * J], ob[4 * J + 1], ob[4 * J + 2], ob[4 * J + 3], wb);
            }
            if (tid == 0) TL(2, 6);
        }
    }
    if (real) return;

    const int tt = tid - 128, tw = warp - 4;
    if (tt == 0) TL(3, 5);
    float* s_red = (float*)(smem + K3_OFF_RED);
    #pragma unroll 1
    for (int pass_ = K3_DRY_T && tw != 7 ? 0 : 1; pass_ < 2; pass_++) {
        asm volatile("" : "+r"(pass_));
        const int pass = __reduce_max_sync(~0u, pass_);
        const int nbid = pass ? 1 : 4, nbar = pass ? 256 : 224;
        if (pass) mbar_wait_warp(barFull + 112, 0);
        if (tt == 0) TL(3, pass ? 6 : 11);
        uint4 wA[10], wB[12];
        #pragma unroll
        for (int i = 0; i < 10; i++) wA[i] = lds_v4(sb + K3_OFF_WG + tw * 5120 + i * 512 + lane * 16);
        #pragma unroll
        for (int i = 0; i < 12; i++) wB[i] = lds_v4(sb + K3_OFF_WD + tw * 6144 + i * 512 + lane * 16);
        if (tw == 0) {
            if (pass) pdl_wait();
            const uint8_t* kp = pass ? g_xc + XC_KEYS + nt * 512 + lane * 16 : dummy + lane * 16;
            uint4 v;
            uint32_t it = 0;
            do {
                unsigned long long u0, u1;
                asm volatile("ld.relaxed.gpu.global.v2.b64 {%0, %1}, [%2];" : "=l"(u0), "=l"(u1) : "l"(kp) : "memory");
                v = make_uint4((uint32_t)(u0 >> 32), (uint32_t)u0, (uint32_t)(u1 >> 32), (uint32_t)u1);
                if (++it > (1u << 22)) __trap();
            } while (pass && !__all_sync(~0u, v.y != ~0u && v.w != ~0u));
            if (tt == 0) { TL(3, pass ? 1 : 8); if (pass) TLC(4, 24); }
            warp_top2(v.x, v.y, v.z, v.w);
            if (lane == 0) *(uint4*)(smem + K3_OFF_SEL) = make_uint4(v.y, v.w, v.x, v.z);
            __syncwarp();
            if (pass) named_arrive<2, 160>();
        }
        named_bar_rr(nbid, nbar);
        if (pass) pdl_wait();
        if (tt == 0) { TL(3, pass ? 2 : 9); if (pass) TLC(4, 25); }
        const uint4 sel = *(const uint4*)(smem + K3_OFF_SEL);
        {
            const int u = tt - 160, tk = tt < 160 ? tt >= 80 : (u >> 2) & 1;
            const uint32_t j = tk ? sel.y : sel.x;
            const uint32_t off = tt < 160 ? (tt - 80 * tk) * 16 : ((u >> 1) & 1) * 1280 + max(b - 88, 0) * 32 + (u & 1) * 16;
            const uint32_t dst = tt < 160 ? sb + K3_OFF_X + tk * K3_XS + off : sb + K3_OFF_HL + (u & 7) * 16;
            const uint8_t* src = pass ? g_xc + XC_CAND + ((j >> 7) * 2 + (j & 1)) * 2560 + off : dummy + tt * 16;
            const bool on = tt < 160 ? b < 96 : (tt < 168 && b >= 88);
            if (on) {
                uint4 v;
                uint32_t it = 0;
                do {
                    v = ldx_v4(src);
                    if (++it > (1u << 22)) __trap();
                } while (pass && !valid4(v));
                sts_v4(dst, v);
            }
        }
        named_bar_rr(nbid, nbar);
        if (tt == 0) { TL(3, pass ? 3 : 10); if (pass) TLC(4, 20); }
        if (b < 96) {
            gemv16<5>(wA, sb + K3_OFF_X + (tw & 3) * 320, K3_XS, s_red + tw * 32, lane);
            if (tt == 0 && pass) TLC(4, 21);
            named_bar_rr(nbid, nbar);
            if (tt == 0 && pass) TLC(4, 22);
            if (tt < 32) {
                const float gb = round_bf((s_red[tt] + s_red[32 + tt]) + (s_red[64 + tt] + s_red[96 + tt]));
                const float ub = round_bf((s_red[128 + tt] + s_red[160 + tt]) + (s_red[192 + tt] + s_red[224 + tt]));
                const float sl = round_bf(__fdividef(gb, 1.f + __expf(-gb)));
                const float v = sl * ub, vn = __shfl_down_sync(~0u, v, 1);
                if (pass && !(tt & 1))
                    asm volatile("st.relaxed.gpu.global.b32 [%0], %1;" :: "l"(g_xc + XC_HF + (tt >> 4) * (F_ * 2) + (b * 16 + (tt & 15)) * 2), "r"(pack_bf(v, vn)) : "memory");
                if (tt == 0) { TL(3, pass ? 4 : 7); if (pass) TLC(4, 23); }
            }
        }
        if (b >= 88) {
            {
                const uint8_t* src = pass ? g_xc + XC_HF + tt * 16 : dummy + tt * 16;
                const bool two = tt < 128;
                uint4 v0, v1;
                uint32_t it = 0;
                do {
                    v0 = ldx_v4(src); v1 = ldx_v4(src + (two ? 4096 : 0));
                    if (++it > (1u << 22)) __trap();
                } while (pass && !(valid4(v0) && valid4(v1)));
                if (pass) {
                    sts_v4(sb + K3_OFF_HF + (tt >= 192 ? K3_HS - F_ * 2 : 0) + tt * 16, v0);
                    if (two) sts_v4(sb + K3_OFF_HF + K3_HS - F_ * 2 + 4096 + tt * 16, v1);
                }
            }
            named_bar_rr(nbid, nbar);
            if (tt == 0) { TL(4, pass ? 1 : 3); if (pass) TLC(4, 16); }
            gemv16<6>(wB, sb + K3_OFF_HF + tw * 384, K3_HS, s_red + tw * 32, lane);
            if (tt == 0 && pass) TLC(4, 17);
            named_bar_rr(nbid, nbar);
            if (tt == 0 && pass) TLC(4, 18);
            if (tt < 32) {
                const int tk = tt >> 4;
                const float y = ((s_red[tt] + s_red[32 + tt]) + (s_red[64 + tt] + s_red[96 + tt])) + ((s_red[128 + tt] + s_red[160 + tt]) + (s_red[192 + tt] + s_red[224 + tt]));
                const float r = round_bf(key_value(tk ? sel.w : sel.z));
                const float sg = round_bf(__fdividef(1.f, 1.f + __expf(-r)));
                const bf16* hl = (const bf16*)(smem + K3_OFF_HL) + tk * 32 + (tt & 15);
                const float ln = __bfloat162float(hl[0]), h = __bfloat162float(hl[16]);
                const float upd = round_bf(round_bf(y) * sg);
                if (pass) out[(size_t)((tk ? sel.y : sel.x) >> 1) * D_ + (b - 88) * 16 + (tt & 15)] = __float2bfloat16_rn(h + round_bf(ln + upd));
                if (tt == 0) { TL(4, pass ? 2 : 4); if (pass) TLC(4, 19); }
            }
        }
    }
}

#define EXP_PROMO CU_TENSOR_MAP_L2_PROMOTION_L2_256B
typedef CUresult (*PFN_encodeTiled)(CUtensorMap*, CUtensorMapDataType, cuuint32_t, void*, const cuuint64_t*, const cuuint64_t*, const cuuint32_t*,
                                    const cuuint32_t*, CUtensorMapInterleave, CUtensorMapSwizzle, CUtensorMapL2promotion, CUtensorMapFloatOOBfill);

static void encode_map(PFN_encodeTiled fn, CUtensorMap* m, const void* base, int rank, const cuuint64_t* dims, const cuuint64_t* strides,
                       const cuuint32_t* box, CUtensorMapSwizzle sw, CUtensorMapL2promotion promo = EXP_PROMO) {
    cuuint32_t es[3] = {1, 1, 1};
    fn(m, CU_TENSOR_MAP_DATA_TYPE_BFLOAT16, rank, (void*)base, dims, strides, box, es, CU_TENSOR_MAP_INTERLEAVE_NONE, sw,
       promo, CU_TENSOR_MAP_FLOAT_OOB_FILL_NONE);
}

template <typename... KArgs, typename... Args>
static void launch(void (*kern)(KArgs...), int grid, int block, int smem, int cluster, bool pdl, Args... args) {
    cudaLaunchConfig_t cfg = {};
    cfg.gridDim = dim3(grid); cfg.blockDim = dim3(block); cfg.dynamicSmemBytes = smem; cfg.stream = cudaStreamPerThread;
    cudaLaunchAttribute at[2]; int n = 0;
    if (cluster > 1) { at[n].id = cudaLaunchAttributeClusterDimension; at[n].val.clusterDim.x = cluster; at[n].val.clusterDim.y = 1; at[n].val.clusterDim.z = 1; n++; }
    if (pdl) { at[n].id = cudaLaunchAttributeProgrammaticStreamSerialization; at[n].val.programmaticStreamSerializationAllowed = 1; n++; }
    cfg.attrs = at; cfg.numAttrs = n;
    cudaLaunchKernelEx(&cfg, kern, args...);
}

extern "C" void kernel_launch(void* const* d_in, const int* in_sizes, int n_in, void* d_out, int out_size) {
    const bf16* x = (const bf16*)d_in[0];
    const bf16* wqkv = (const bf16*)d_in[1];
    const bf16* wo = (const bf16*)d_in[2];
    const bf16* wr = (const bf16*)d_in[4];
    const bf16* wgate = (const bf16*)d_in[5];
    const bf16* wup = (const bf16*)d_in[6];
    const bf16* wdown = (const bf16*)d_in[7];
    bf16* out = (bf16*)d_out;

    static PFN_encodeTiled enc = nullptr;
    static void* o_ptr = nullptr;
    if (!enc) {
        cudaDriverEntryPointQueryResult qr;
        void* fn = nullptr;
        cudaGetDriverEntryPoint("cuTensorMapEncodeTiled", &fn, cudaEnableDefault, &qr);
        enc = (PFN_encodeTiled)fn;
        cudaGetSymbolAddress(&o_ptr, g_o);
        cudaFuncSetAttribute(k1_qkv, cudaFuncAttributeMaxDynamicSharedMemorySize, K1_SMEM);
        cudaFuncSetAttribute(k2_attn, cudaFuncAttributeMaxDynamicSharedMemorySize, K2_SMEM);
        cudaFuncSetAttribute(k3_tail, cudaFuncAttributeMaxDynamicSharedMemorySize, K3_SMEM);
    }
    CUtensorMap tmX, tmW, tmO, tmG, tmU, tmD;
    { cuuint64_t d[2] = {640, 2048}, s[1] = {1280}; cuuint32_t b[2] = {64, 128}; encode_map(enc, &tmX, x, 2, d, s, b, CU_TENSOR_MAP_SWIZZLE_128B); }
    { cuuint64_t d[2] = {1920, 640}, s[1] = {3840}; cuuint32_t b[2] = {64, 64}; encode_map(enc, &tmW, wqkv, 2, d, s, b, CU_TENSOR_MAP_SWIZZLE_128B); }
    { cuuint64_t d[2] = {640, 2048}, s[1] = {1280}; cuuint32_t b[2] = {64, 64}; encode_map(enc, &tmO, o_ptr, 2, d, s, b, CU_TENSOR_MAP_SWIZZLE_128B); }

    { cuuint64_t d[2] = {1536, 640}, s[1] = {3072}; cuuint32_t b[2] = {64, 160}; encode_map(enc, &tmG, wgate, 2, d, s, b, CU_TENSOR_MAP_SWIZZLE_128B);
      encode_map(enc, &tmU, wup, 2, d, s, b, CU_TENSOR_MAP_SWIZZLE_128B); }
    { cuuint64_t d[2] = {640, 1536}, s[1] = {1280}; cuuint32_t b[2] = {64, 192}; encode_map(enc, &tmD, wdown, 2, d, s, b, CU_TENSOR_MAP_SWIZZLE_128B); }

    launch(k1_qkv, 128, 384, K1_SMEM, 2, false, tmX, tmW, x, wqkv, wo);
    launch(k2_attn, 128 + K2_MOVERS, 512, K2_SMEM, 1, true, tmG, tmU, tmD, 0x007F007Fu, 0xFF80FF80u);
    launch(k3_tail, 128, 384, K3_SMEM, 2, true, tmO, x, wr, wgate, out);
}
```

```cpp
#include <cuda_runtime.h>
#include <cuda_bf16.h>
#include <cuda.h>
#include <stdint.h>

typedef __nv_bfloat16 bf16;

constexpr int S_ = 2048, D_ = 640, H_ = 32, F_ = 1536;
constexpr int HEAD_BYTES = 256 * 384;
constexpr uint32_t POLYMASK = 0xADADu;
constexpr float QSCALE = 0.22360679774997896f * 1.4426950408889634f;

__device__ __align__(1024) uint8_t g_qkv[3 * H_ * HEAD_BYTES];
__device__ float g_kmax[H_ * 128];
__device__ __align__(16) ulonglong2 g_rowstat[S_];
__device__ __align__(16) unsigned long long g_colsum[3 * D_];
__device__ unsigned g_epoch;
__device__ __align__(1024) bf16 g_o[S_ * D_];
constexpr int XC_PART = 0;
constexpr int XC_KEYS = XC_PART + S_ * 64;
constexpr int XC_CAND = XC_KEYS + 4 * 32 * 16;
constexpr int XC_HF = XC_CAND + 32 * 2 * 2560;
constexpr int XC_BYTES = XC_HF + 2 * F_ * 2;
static_assert(XC_BYTES == 128 * 148 * 16, "K2 resets 148 x 16 bytes per CTA");
__device__ __align__(1024) uint8_t g_xc[XC_BYTES];
__device__ __align__(1024) uint8_t g_wimg[3 * D_ * F_ * 2];
__device__ __align__(1024) uint8_t g_wo_img[D_ * D_ * 2];

#define TL(k, slot) do {} while (0)
#define TLC(k, slot) do {} while (0)
__device__ __forceinline__ uint32_t smem_u32(const void* p) { return (uint32_t)__cvta_generic_to_shared(p); }
__device__ __forceinline__ uint64_t make_desc(uint32_t lo, uint32_t hi) {
    uint64_t d; asm("mov.b64 %0, {%1, %2};" : "=l"(d) : "r"(lo), "r"(hi));
    return d;
}
__device__ __forceinline__ void wg_fence() { asm volatile("wgmma.fence.sync.aligned;" ::: "memory"); }
__device__ __forceinline__ void wg_commit() { asm volatile("wgmma.commit_group.sync.aligned;" ::: "memory"); }
template<int N> __device__ __forceinline__ void wg_wait() { asm volatile("wgmma.wait_group.sync.aligned %0;" :: "n"(N) : "memory"); }
__device__ __forceinline__ void mbar_init(uint32_t bar, uint32_t cnt) { asm volatile("mbarrier.init.shared::cta.b64 [%0], %1;" :: "r"(bar), "r"(cnt)); }
__device__ __forceinline__ void mbar_expect_tx(uint32_t bar, uint32_t bytes) { asm volatile("mbarrier.arrive.expect_tx.shared::cta.b64 _, [%0], %1;" :: "r"(bar), "r"(bytes) : "memory"); }
__device__ __forceinline__ void mbar_arrive(uint32_t bar) { asm volatile("mbarrier.arrive.shared::cta.b64 _, [%0];" :: "r"(bar) : "memory"); }
__device__ __forceinline__ void mbar_arrive_cluster(uint32_t bar, uint32_t cta) {
    asm volatile("{\n.reg .b32 ra;\nmapa.shared::cluster.u32 ra, %0, %1;\n"
                 "mbarrier.arrive.shared::cluster.b64 _, [ra];\n}\n" :: "r"(bar), "r"(cta) : "memory");
}
__device__ __forceinline__ void mbar_wait(uint32_t bar, uint32_t parity) {
    asm volatile("{\n"
        ".reg .pred p;\n.reg .u32 c;\n"
        "mov.u32 c, 0;\n"
        "WAIT_LOOP:\n"
        "mbarrier.try_wait.parity.shared::cta.b64 p, [%0], %1;\n"
        "@p bra WAIT_DONE;\n"
        "add.u32 c, c, 1;\n"
        "setp.lt.u32 p, c, 0x1000000;\n"
        "@p bra WAIT_LOOP;\n"
        "trap;\n"
        "WAIT_DONE:\n"
        "}\n" :: "r"(bar), "r"(parity) : "memory");
}
__device__ __forceinline__ void mbar_wait_warp(uint32_t bar, uint32_t parity) {
    asm volatile("{\n"
        ".reg .pred p, q;\n.reg .u32 c;\n"
        "mov.u32 c, 0;\n"
        "WAIT_LOOP:\n"
        "mbarrier.try_wait.parity.shared::cta.b64 p, [%0], %1;\n"
        "vote.sync.all.pred p, p, 0xffffffff;\n"
        "@p bra.uni WAIT_DONE;\n"
        "add.u32 c, c, 1;\n"
        "setp.lt.u32 q, c, 0x1000000;\n"
        "@q bra.uni WAIT_LOOP;\n"
        "trap;\n"
        "WAIT_DONE:\n"
        "}\n" :: "r"(bar), "r"(parity) : "memory");
}
__device__ __forceinline__ void mbar_wait_cluster(uint32_t bar, uint32_t parity) {
    asm volatile("{\n"
        ".reg .pred p;\n.reg .u32 c;\n"
        "mov.u32 c, 0;\n"
        "WAIT_LOOP:\n"
        "mbarrier.try_wait.parity.acquire.cluster.shared::cta.b64 p, [%0], %1;\n"
        "@p bra WAIT_DONE;\n"
        "add.u32 c, c, 1;\n"
        "setp.lt.u32 p, c, 0x1000000;\n"
        "@p bra WAIT_LOOP;\n"
        "trap;\n"
        "WAIT_DONE:\n"
        "}\n" :: "r"(bar), "r"(parity) : "memory");
}
__device__ __forceinline__ void fence_mbar_init() { asm volatile("fence.mbarrier_init.release.cluster;" ::: "memory"); }
__device__ __forceinline__ void fence_async_smem() { asm volatile("fence.proxy.async.shared::cta;" ::: "memory"); }
__device__ __forceinline__ void bulk_g2s(uint32_t dst, const void* src, uint32_t bytes, uint32_t bar) {
    asm volatile("cp.async.bulk.shared::cluster.global.mbarrier::complete_tx::bytes [%0], [%1], %2, [%3];" :: "r"(dst), "l"(src), "r"(bytes), "r"(bar) : "memory");
}
__device__ __forceinline__ void bulk_g2s_mc(uint32_t dst, const void* src, uint32_t bytes, uint32_t bar, uint16_t mask) {
    asm volatile("cp.async.bulk.shared::cluster.global.mbarrier::complete_tx::bytes.multicast::cluster [%0], [%1], %2, [%3], %4;"
        :: "r"(dst), "l"(src), "r"(bytes), "r"(bar), "h"(mask) : "memory");
}
__device__ __forceinline__ void bulk_s2g(void* dst, uint32_t src, uint32_t bytes) {
    asm volatile("cp.async.bulk.global.shared::cta.bulk_group [%0], [%1], %2;" :: "l"(dst), "r"(src), "r"(bytes) : "memory");
}
__device__ __forceinline__ void bulk_commit() { asm volatile("cp.async.bulk.commit_group;" ::: "memory"); }
__device__ __forceinline__ void bulk_wait_all() { asm volatile("cp.async.bulk.wait_group 0;" ::: "memory"); }
__device__ __forceinline__ void prefetch_l2(const void* p, uint32_t bytes) {
    asm volatile("cp.async.bulk.prefetch.L2.global [%0], %1;" :: "l"(p), "r"(bytes) : "memory");
}
__device__ __forceinline__ void tma_2d(uint32_t dst, const CUtensorMap* tm, int c0, int c1, uint32_t bar) {
    asm volatile("cp.async.bulk.tensor.2d.shared::cluster.global.mbarrier::complete_tx::bytes [%0], [%1, {%3, %4}], [%2];"
        :: "r"(dst), "l"(tm), "r"(bar), "r"(c0), "r"(c1) : "memory");
}
__device__ __forceinline__ void tma_2d_mc(uint32_t dst, const CUtensorMap* tm, int c0, int c1, uint32_t bar, uint16_t mask) {
    asm volatile("cp.async.bulk.tensor.2d.shared::cluster.global.mbarrier::complete_tx::bytes.multicast::cluster [%0], [%1, {%3, %4}], [%2], %5;"
        :: "r"(dst), "l"(tm), "r"(bar), "r"(c0), "r"(c1), "h"(mask) : "memory");
}
__device__ __forceinline__ void tma_3d(uint32_t dst, const CUtensorMap* tm, int c0, int c1, int c2, uint32_t bar) {
    asm volatile("cp.async.bulk.tensor.3d.shared::cluster.global.mbarrier::complete_tx::bytes [%0], [%1, {%3, %4, %5}], [%2];"
        :: "r"(dst), "l"(tm), "r"(bar), "r"(c0), "r"(c1), "r"(c2) : "memory");
}
__device__ __forceinline__ void tmap_prefetch(const CUtensorMap* tm) { asm volatile("prefetch.tensormap [%0];" :: "l"(tm) : "memory"); }
__device__ __forceinline__ void cluster_arrive() { asm volatile("barrier.cluster.arrive.relaxed.aligned;" ::: "memory"); }
__device__ __forceinline__ void cluster_wait() { asm volatile("barrier.cluster.wait.acquire.aligned;" ::: "memory"); }
template<int ID, int N> __device__ __forceinline__ void named_bar() { asm volatile("bar.sync %0, %1;" :: "n"(ID), "n"(N) : "memory"); }
__device__ __forceinline__ void pdl_launch() { asm volatile("griddepcontrol.launch_dependents;" ::: "memory"); }
__device__ __forceinline__ void pdl_wait() { asm volatile("griddepcontrol.wait;" ::: "memory"); }
__device__ __forceinline__ uint4 ldg_v4(const void* p) {
    uint4 v; asm volatile("ld.relaxed.gpu.global.v4.b32 {%0,%1,%2,%3}, [%4];" : "=r"(v.x), "=r"(v.y), "=r"(v.z), "=r"(v.w) : "l"(p)); return v;
}
__device__ __forceinline__ uint32_t ldg_b32(const void* p) {
    uint32_t v; asm volatile("ld.relaxed.gpu.global.b32 %0, [%1];" : "=r"(v) : "l"(p)); return v;
}
__device__ __forceinline__ void st_tagged(void* p, float v, uint32_t tag) {
    asm volatile("st.relaxed.gpu.global.b64 [%0], %1;" :: "l"(p), "l"(((unsigned long long)tag << 32) | __float_as_uint(v)) : "memory");
}
__device__ __forceinline__ void st_tagged2(void* p, float v0, float v1, uint32_t tag) {
    asm volatile("st.relaxed.gpu.global.v2.b64 [%0], {%1, %2};" :: "l"(p), "l"(((unsigned long long)tag << 32) | __float_as_uint(v0)),
                 "l"(((unsigned long long)tag << 32) | __float_as_uint(v1)) : "memory");
}
__device__ __forceinline__ uint4 ld_tagged2(const void* p) {
    unsigned long long a, b;
    asm volatile("ld.relaxed.gpu.global.v2.b64 {%0, %1}, [%2];" : "=l"(a), "=l"(b) : "l"(p) : "memory");
    return make_uint4((uint32_t)a, (uint32_t)(a >> 32), (uint32_t)b, (uint32_t)(b >> 32));
}
__device__ __forceinline__ void stmatrix_x4(uint32_t addr, uint32_t r0, uint32_t r1, uint32_t r2, uint32_t r3) {
    asm volatile("stmatrix.sync.aligned.m8n8.x4.shared.b16 [%0], {%1, %2, %3, %4};" :: "r"(addr), "r"(r0), "r"(r1), "r"(r2), "r"(r3) : "memory");
}
__device__ __forceinline__ void named_bar_rr(int id, int n) { asm volatile("bar.sync %0, %1;" :: "r"(id), "r"(n) : "memory"); }
template<int ID, int N> __device__ __forceinline__ void named_arrive() { asm volatile("bar.arrive %0, %1;" :: "n"(ID), "n"(N) : "memory"); }
__device__ __forceinline__ void bulk_wait_read() { asm volatile("cp.async.bulk.wait_group.read 0;" ::: "memory"); }
__device__ __forceinline__ uint4 lds_v4(uint32_t a) {
    uint4 v; asm volatile("ld.shared.v4.b32 {%0,%1,%2,%3}, [%4];" : "=r"(v.x), "=r"(v.y), "=r"(v.z), "=r"(v.w) : "r"(a) : "memory"); return v;
}
__device__ __forceinline__ void sts_v4(uint32_t a, const uint4 v) {
    asm volatile("st.shared.v4.b32 [%0], {%1,%2,%3,%4};" :: "r"(a), "r"(v.x), "r"(v.y), "r"(v.z), "r"(v.w) : "memory");
}
__device__ __forceinline__ float bf_lo(uint32_t v) { return __uint_as_float(v << 16); }
__device__ __forceinline__ float bf_hi(uint32_t v) { return __uint_as_float(v & 0xffff0000u); }
__device__ __forceinline__ uint32_t pack_bf(float lo, float hi) {
    uint32_t r; asm("cvt.rn.bf16x2.f32 %0, %1, %2;" : "=r"(r) : "f"(hi), "f"(lo)); return r;
}
__device__ __forceinline__ float round_bf(float x) { return __uint_as_float(pack_bf(0.f, x)); }

__device__ __forceinline__ void mma_n240_ss(float (&d)[120], uint64_t da, uint64_t db, int scale_d) {
    asm volatile("{\n.reg .pred p;\nsetp.ne.b32 p, %122, 0;\n"
        "wgmma.mma_async.sync.aligned.m64n240k16.f32.bf16.bf16 "
        "{%0,%1,%2,%3,%4,%5,%6,%7,%8,%9,%10,%11,%12,%13,%14,%15,%16,%17,%18,%19,%20,%21,%22,%23,%24,%25,%26,%27,%28,%29,%30,%31,%32,%33,%34,%35,%36,%37,%38,%39,%40,%41,%42,%43,%44,%45,%46,%47,%48,%49,%50,%51,%52,%53,%54,%55,%56,%57,%58,%59,%60,%61,%62,%63,%64,%65,%66,%67,%68,%69,%70,%71,%72,%73,%74,%75,%76,%77,%78,%79,%80,%81,%82,%83,%84,%85,%86,%87,%88,%89,%90,%91,%92,%93,%94,%95,%96,%97,%98,%99,%100,%101,%102,%103,%104,%105,%106,%107,%108,%109,%110,%111,%112,%113,%114,%115,%116,%117,%118,%119}, %120, %121, p, 1, 1, 0, 1;\n}\n"
        : "+f"(d[0]), "+f"(d[1]), "+f"(d[2]), "+f"(d[3]), "+f"(d[4]), "+f"(d[5]), "+f"(d[6]), "+f"(d[7]), "+f"(d[8]), "+f"(d[9]), "+f"(d[10]), "+f"(d[11]), "+f"(d[12]), "+f"(d[13]), "+f"(d[14]), "+f"(d[15]), "+f"(d[16]), "+f"(d[17]), "+f"(d[18]), "+f"(d[19]), "+f"(d[20]), "+f"(d[21]), "+f"(d[22]), "+f"(d[23]), "+f"(d[24]), "+f"(d[25]), "+f"(d[26]), "+f"(d[27]), "+f"(d[28]), "+f"(d[29]), "+f"(d[30]), "+f"(d[31]), "+f"(d[32]), "+f"(d[33]), "+f"(d[34]), "+f"(d[35]), "+f"(d[36]), "+f"(d[37]), "+f"(d[38]), "+f"(d[39]), "+f"(d[40]), "+f"(d[41]), "+f"(d[42]), "+f"(d[43]), "+f"(d[44]), "+f"(d[45]), "+f"(d[46]), "+f"(d[47]), "+f"(d[48]), "+f"(d[49]), "+f"(d[50]), "+f"(d[51]), "+f"(d[52]), "+f"(d[53]), "+f"(d[54]), "+f"(d[55]), "+f"(d[56]), "+f"(d[57]), "+f"(d[58]), "+f"(d[59]), "+f"(d[60]), "+f"(d[61]), "+f"(d[62]), "+f"(d[63]), "+f"(d[64]), "+f"(d[65]), "+f"(d[66]), "+f"(d[67]), "+f"(d[68]), "+f"(d[69]), "+f"(d[70]), "+f"(d[71]), "+f"(d[72]), "+f"(d[73]), "+f"(d[74]), "+f"(d[75]), "+f"(d[76]), "+f"(d[77]), "+f"(d[78]), "+f"(d[79]), "+f"(d[80]), "+f"(d[81]), "+f"(d[82]), "+f"(d[83]), "+f"(d[84]), "+f"(d[85]), "+f"(d[86]), "+f"(d[87]), "+f"(d[88]), "+f"(d[89]), "+f"(d[90]), "+f"(d[91]), "+f"(d[92]), "+f"(d[93]), "+f"(d[94]), "+f"(d[95]), "+f"(d[96]), "+f"(d[97]), "+f"(d[98]), "+f"(d[99]), "+f"(d[100]), "+f"(d[101]), "+f"(d[102]), "+f"(d[103]), "+f"(d[104]), "+f"(d[105]), "+f"(d[106]), "+f"(d[107]), "+f"(d[108]), "+f"(d[109]), "+f"(d[110]), "+f"(d[111]), "+f"(d[112]), "+f"(d[113]), "+f"(d[114]), "+f"(d[115]), "+f"(d[116]), "+f"(d[117]), "+f"(d[118]), "+f"(d[119])
        : "l"(da), "l"(db), "r"(scale_d));
}

__device__ __forceinline__ void mma_n160_ss(float (&d)[80], uint64_t da, uint64_t db, int scale_d) {
    asm volatile("{\n.reg .pred p;\nsetp.ne.b32 p, %82, 0;\n"
        "wgmma.mma_async.sync.aligned.m64n160k16.f32.bf16.bf16 "
        "{%0,%1,%2,%3,%4,%5,%6,%7,%8,%9,%10,%11,%12,%13,%14,%15,%16,%17,%18,%19,%20,%21,%22,%23,%24,%25,%26,%27,%28,%29,%30,%31,%32,%33,%34,%35,%36,%37,%38,%39,%40,%41,%42,%43,%44,%45,%46,%47,%48,%49,%50,%51,%52,%53,%54,%55,%56,%57,%58,%59,%60,%61,%62,%63,%64,%65,%66,%67,%68,%69,%70,%71,%72,%73,%74,%75,%76,%77,%78,%79}, %80, %81, p, 1, 1, 0, 1;\n}\n"
        : "+f"(d[0]), "+f"(d[1]), "+f"(d[2]), "+f"(d[3]), "+f"(d[4]), "+f"(d[5]), "+f"(d[6]), "+f"(d[7]), "+f"(d[8]), "+f"(d[9]), "+f"(d[10]), "+f"(d[11]), "+f"(d[12]), "+f"(d[13]), "+f"(d[14]), "+f"(d[15]), "+f"(d[16]), "+f"(d[17]), "+f"(d[18]), "+f"(d[19]), "+f"(d[20]), "+f"(d[21]), "+f"(d[22]), "+f"(d[23]), "+f"(d[24]), "+f"(d[25]), "+f"(d[26]), "+f"(d[27]), "+f"(d[28]), "+f"(d[29]), "+f"(d[30]), "+f"(d[31]), "+f"(d[32]), "+f"(d[33]), "+f"(d[34]), "+f"(d[35]), "+f"(d[36]), "+f"(d[37]), "+f"(d[38]), "+f"(d[39]), "+f"(d[40]), "+f"(d[41]), "+f"(d[42]), "+f"(d[43]), "+f"(d[44]), "+f"(d[45]), "+f"(d[46]), "+f"(d[47]), "+f"(d[48]), "+f"(d[49]), "+f"(d[50]), "+f"(d[51]), "+f"(d[52]), "+f"(d[53]), "+f"(d[54]), "+f"(d[55]), "+f"(d[56]), "+f"(d[57]), "+f"(d[58]), "+f"(d[59]), "+f"(d[60]), "+f"(d[61]), "+f"(d[62]), "+f"(d[63]), "+f"(d[64]), "+f"(d[65]), "+f"(d[66]), "+f"(d[67]), "+f"(d[68]), "+f"(d[69]), "+f"(d[70]), "+f"(d[71]), "+f"(d[72]), "+f"(d[73]), "+f"(d[74]), "+f"(d[75]), "+f"(d[76]), "+f"(d[77]), "+f"(d[78]), "+f"(d[79])
        : "l"(da), "l"(db), "r"(scale_d));
}

#define D8(d,o) "+f"(d[o+0]), "+f"(d[o+1]), "+f"(d[o+2]), "+f"(d[o+3]), "+f"(d[o+4]), "+f"(d[o+5]), "+f"(d[o+6]), "+f"(d[o+7])
template<int SCALE_D>
__device__ __forceinline__ void mma_n64_rs(float (&d)[32], uint32_t a0, uint32_t a1, uint32_t a2, uint32_t a3, uint64_t db) {
    asm volatile("{\n"
        "wgmma.mma_async.sync.aligned.m64n64k16.f32.bf16.bf16 "
        "{%0,%1,%2,%3,%4,%5,%6,%7,%8,%9,%10,%11,%12,%13,%14,%15,"
        "%16,%17,%18,%19,%20,%21,%22,%23,%24,%25,%26,%27,%28,%29,%30,%31}, {%32,%33,%34,%35}, %36, %37, 1, 1, 0;\n}\n"
        : D8(d,0), D8(d,8), D8(d,16), D8(d,24)
        : "r"(a0), "r"(a1), "r"(a2), "r"(a3), "l"(db), "n"(SCALE_D));
}
template<int SCALE_D>
__device__ __forceinline__ void mma_n24_rs(float (&d)[12], uint32_t a0, uint32_t a1, uint32_t a2, uint32_t a3, uint64_t db) {
    asm volatile("{\n"
        "wgmma.mma_async.sync.aligned.m64n24k16.f32.bf16.bf16 "
        "{%0,%1,%2,%3,%4,%5,%6,%7,%8,%9,%10,%11}, {%12,%13,%14,%15}, %16, %17, 1, 1, 1;\n}\n"
        : "+f"(d[0]), "+f"(d[1]), "+f"(d[2]), "+f"(d[3]), "+f"(d[4]), "+f"(d[5]), "+f"(d[6]), "+f"(d[7]),
          "+f"(d[8]), "+f"(d[9]), "+f"(d[10]), "+f"(d[11])
        : "r"(a0), "r"(a1), "r"(a2), "r"(a3), "l"(db), "n"(SCALE_D));
}

constexpr int K1_STAGE = 49152, K1_NST = 4;
constexpr int K1_OFF_CS = K1_NST * K1_STAGE;
constexpr int K1_OFF_RS = K1_OFF_CS + 1024;
constexpr int K1_OFF_PART = K1_OFF_RS + 1024;
constexpr int K1_OFF_BAR = K1_OFF_PART + 256;
constexpr int K1_SMEM = K1_OFF_BAR + 128;
constexpr uint32_t KAUX0 = 0x43C03F80u, KAUX1 = 0x3B2CBFCDu;

template<int P> __device__ __forceinline__ void k1_store_pair(uint32_t sb, int nt, int mt) {
    named_bar<5 + P, 288>();
    if ((threadIdx.x & 31) < 2) {
        const int hl = 2 * P + (threadIdx.x & 31);
        bulk_s2g(g_qkv + (size_t)(nt * 12 + hl) * HEAD_BYTES + mt * 6144, sb + hl * 6144, 6144);
        bulk_commit();
    }
}

__global__ void __launch_bounds__(384, 1)
k1_qkv(const __grid_constant__ CUtensorMap tmX, const __grid_constant__ CUtensorMap tmW, const bf16* __restrict__ x, const bf16* __restrict__ W,
       const bf16* __restrict__ wo) {
    extern __shared__ __align__(1024) uint8_t smem[];
    const uint32_t sb = smem_u32(smem);
    const uint32_t barFull = sb + K1_OFF_BAR, barEmpty = barFull + 32, barStat = barFull + 64;
    const int tid = threadIdx.x, warp = tid >> 5, lane = tid & 31;
    uint32_t rank; asm("mov.u32 %0, %%cluster_ctarank;" : "=r"(rank));
    const int pair = blockIdx.x >> 1, nt = pair & 7, mt = (pair >> 3) * 2 + (int)rank;
    pdl_launch();
    if (tid == 0) TL(0, 0);

    if (warp == 8) {
        if (lane == 0) {
            tmap_prefetch(&tmX);
            tmap_prefetch(&tmW);
            for (int s = 0; s < K1_NST; s++) { mbar_init(barFull + 8 * s, 1); mbar_init(barEmpty + 8 * s, 4); }
            mbar_init(barStat, 3);
            fence_mbar_init();
            fence_async_smem();
            mbar_expect_tx(barFull, K1_STAGE);
            tma_2d(sb, &tmX, 0, mt * 128, barFull);
            for (int s = 1; s < K1_NST; s++) mbar_expect_tx(barFull + 8 * s, K1_STAGE);
        }
        __syncwarp();
        if (lane == 0) TL(0, 6);
        cluster_arrive();
        cluster_wait();
        if (lane == 0) TL(0, 7);
        if (lane == 0) {
            const int a = 2 * (int)rank;
            for (int kt = 0; kt < 10; kt++) {
                const int s = kt & 3;
                const uint32_t st = sb + s * K1_STAGE, bar = barFull + 8 * s;
                if (kt >= K1_NST) {
                    mbar_wait(barEmpty + 8 * s, ((kt >> 2) - 1) & 1);
                    mbar_expect_tx(bar, K1_STAGE);
                }
                tma_2d_mc(st + 16384 + a * 8192, &tmW, nt * 240 + a * 64, kt * 64, bar, (uint16_t)3);
                tma_2d_mc(st + 16384 + (a + 1) * 8192, &tmW, nt * 240 + (a + 1) * 64, kt * 64, bar, (uint16_t)3);
                if (kt > 0) tma_2d(st, &tmX, kt * 64, mt * 128, bar);
                TL(0, 20 + kt);
            }
        }
        __syncwarp();
        k1_store_pair<0>(sb, nt, mt);
        k1_store_pair<4>(sb, nt, mt);
        bulk_wait_read();
    } else if (warp > 8) {
        cluster_arrive();
        const int hw = warp - 9, b = blockIdx.x;
        uint4 wv[14], xv[15];
        #pragma unroll
        for (int i = 0; i < 3; i++) {
            const int p = hw + 3 * i;
            #pragma unroll
            for (int c = 0; c < 5; c++) {
                xv[i * 5 + c] = make_uint4(0, 0, 0, 0);
                if (p < 8) xv[i * 5 + c] = ldg_v4((const uint4*)(x + (size_t)(b * 16 + 2 * p + (lane >> 4)) * D_) + (lane & 15) + 16 * c);
            }
        }
        #pragma unroll
        for (int i = 0; i < 14; i++) {
            const int it = hw + 3 * i;
            wv[i] = make_uint4(0, 0, 0, 0);
            if (b < 120 && it < 40) wv[i] = ldg_v4((const uint4*)(W + (size_t)(it * 16 + (lane >> 1)) * 1920 + b * 16 + (lane & 1) * 8));
        }
        const uint32_t tag = ldg_b32(&g_epoch) + 1;
        #pragma unroll
        for (int i = 0; i < 3; i++) {
            const int p = hw + 3 * i;
            float s = 0.f;
            #pragma unroll
            for (int c = 0; c < 5; c++) {
                const uint4 v = xv[i * 5 + c];
                s += (bf_lo(v.x) + bf_hi(v.x)) + (bf_lo(v.y) + bf_hi(v.y)) + (bf_lo(v.z) + bf_hi(v.z)) + (bf_lo(v.w) + bf_hi(v.w));
            }
            #pragma unroll
            for (int o = 1; o < 16; o <<= 1) s += __shfl_xor_sync(~0u, s, o);
            const float mu = s * (1.f / D_);
            float q = 0.f;
            #pragma unroll
            for (int c = 0; c < 5; c++) {
                const uint4 v = xv[i * 5 + c];
                float d;
                d = bf_lo(v.x) - mu; q += d * d; d = bf_hi(v.x) - mu; q += d * d;
                d = bf_lo(v.y) - mu; q += d * d; d = bf_hi(v.y) - mu; q += d * d;
                d = bf_lo(v.z) - mu; q += d * d; d = bf_hi(v.z) - mu; q += d * d;
                d = bf_lo(v.w) - mu; q += d * d; d = bf_hi(v.w) - mu; q += d * d;
            }
            #pragma unroll
            for (int o = 1; o < 16; o <<= 1) q += __shfl_xor_sync(~0u, q, o);
            if (p < 8 && (lane & 15) == 0) st_tagged2(&g_rowstat[b * 16 + 2 * p + (lane >> 4)], mu, rsqrtf(q * (1.f / D_) + 1e-5f), tag);
        }
        if (tid == 288) { TL(0, 8); prefetch_l2((const uint8_t*)wo + b * 6400, 6400); }
        float cs[8];
        #pragma unroll
        for (int j = 0; j < 8; j++) cs[j] = 0.f;
        #pragma unroll
        for (int i = 0; i < 14; i++) {
            cs[0] += bf_lo(wv[i].x); cs[1] += bf_hi(wv[i].x); cs[2] += bf_lo(wv[i].y); cs[3] += bf_hi(wv[i].y);
            cs[4] += bf_lo(wv[i].z); cs[5] += bf_hi(wv[i].z); cs[6] += bf_lo(wv[i].w); cs[7] += bf_hi(wv[i].w);
        }
        #pragma unroll
        for (int j = 0; j < 8; j++) {
            #pragma unroll
            for (int o = 2; o < 32; o <<= 1) cs[j] += __shfl_xor_sync(~0u, cs[j], o);
        }
        float* part = (float*)(smem + K1_OFF_PART);
        if (lane < 2) {
            #pragma unroll
            for (int j = 0; j < 8; j++) part[hw * 16 + lane * 8 + j] = cs[j];
        }
        named_bar<2, 96>();
        const int ht = tid - 288;
        if (ht < 16 && b < 120) st_tagged(&g_colsum[b * 16 + ht], part[ht] + part[16 + ht] + part[32 + ht], tag);
        if (tid == 288) TL(0, 9);
        float* scs = (float*)(smem + K1_OFF_CS);
        float2* srs = (float2*)(smem + K1_OFF_RS);
        {
            const bool hr = ht < 32, hc = ht < 24;
            uint4 r0, r1, c0, c1;
            int it = 0;
            bool ok;
            do {
                r0 = ld_tagged2(&g_rowstat[mt * 128 + ht]);
                c0 = ld_tagged2(&g_colsum[nt * 240 + 2 * ht]);
                r1 = hr ? ld_tagged2(&g_rowstat[mt * 128 + 96 + ht]) : r0;
                c1 = hc ? ld_tagged2(&g_colsum[nt * 240 + 192 + 2 * ht]) : c0;
                ok = r0.y == tag && r0.w == tag && c0.y == tag && c0.w == tag && r1.y == tag && r1.w == tag && c1.y == tag && c1.w == tag;
                if (++it > (1 << 22)) __trap();
            } while (!ok);
            srs[ht] = make_float2(__uint_as_float(r0.x), __uint_as_float(r0.z));
            *(float2*)(scs + 2 * ht) = make_float2(__uint_as_float(c0.x), __uint_as_float(c0.z));
            if (hr) srs[96 + ht] = make_float2(__uint_as_float(r1.x), __uint_as_float(r1.z));
            if (hc) *(float2*)(scs + 192 + 2 * ht) = make_float2(__uint_as_float(c1.x), __uint_as_float(c1.z));
        }
        __syncwarp();
        if (lane == 0) mbar_arrive(barStat);
        if (ht == 0) TL(0, 5);
        uint4 wt[2][4];
        #pragma unroll
        for (int i = 0; i < 2; i++) {
            const int item = b * 100 + ht + 96 * i, k = ((item >> 3) / 20) * 8 + (item & 7), grp = (item >> 3) % 20;
            if (i == 0 || ht < 4) {
                #pragma unroll
                for (int c = 0; c < 4; c++) wt[i][c] = ldg_v4(wo + (size_t)k * D_ + grp * 32 + c * 8);
            }
        }
        #pragma unroll
        for (int i = 0; i < 2; i++) {
            const int item = b * 100 + ht + 96 * i, k = ((item >> 3) / 20) * 8 + (item & 7), grp = (item >> 3) % 20;
            if (i == 0 || ht < 4) {
                uint8_t* dst = g_wo_img + ((grp / 5) * 10 + (k >> 6)) * 20480 + ((k >> 3) & 7) * 2560 + (grp % 5) * 512 + (k & 7) * 16;
                *(uint4*)(dst) = make_uint4(wt[i][0].x, wt[i][1].x, wt[i][2].x, wt[i][3].x);
                *(uint4*)(dst + 128) = make_uint4(wt[i][0].y, wt[i][1].y, wt[i][2].y, wt[i][3].y);
                *(uint4*)(dst + 256) = make_uint4(wt[i][0].z, wt[i][1].z, wt[i][2].z, wt[i][3].z);
                *(uint4*)(dst + 384) = make_uint4(wt[i][0].w, wt[i][1].w, wt[i][2].w, wt[i][3].w);
            }
        }
        cluster_wait();
        if (hw == 0) { k1_store_pair<1>(sb, nt, mt); k1_store_pair<5>(sb, nt, mt); }
        else if (hw == 1) k1_store_pair<2>(sb, nt, mt);
        else k1_store_pair<3>(sb, nt, mt);
        bulk_wait_read();
    } else {
        cluster_arrive();
        cluster_wait();
        const int wg = warp >> 2, w4 = warp & 3, g = lane >> 2, t = lane & 3;
        float acc[120];
        const uint32_t hiA = 64u | (1u << 30), hiB = 64u | (1u << 30);
        #pragma unroll 1
        for (int kt = 0; kt < 10; kt++) {
            const int s = kt & 3;
            const uint32_t st = sb + s * K1_STAGE;
            mbar_wait(barFull + 8 * s, (kt >> 2) & 1);
            if (tid == 0 && kt == 0) TL(0, 1);
            if (tid == 0) TL(0, 10 + kt);
            const uint32_t sa = (st & 0x3FFFF) >> 4;
            const uint32_t loA = sa + wg * 512 + (1u << 16), loB = sa + 1024 + (512u << 16);
            wg_fence();
            #pragma unroll
            for (int kk = 0; kk < 4; kk++)
                mma_n240_ss(acc, make_desc(loA + 2 * kk, hiA), make_desc(loB + 128 * kk, hiB), (kt | kk) != 0);
            wg_commit();
            if (kt > 0) {
                wg_wait<1>();
                if (kt <= 6 && (tid & 127) == 0) {
                    const uint32_t eb = barEmpty + 8 * ((kt - 1) & 3);
                    mbar_arrive_cluster(eb, 0);
                    mbar_arrive_cluster(eb, 1);
                }
            }
        }
        wg_wait<0>();
        #pragma unroll
        for (int i = 0; i < 120; i++) asm volatile("" : "+f"(acc[i]) :: "memory");
        if (tid == 0) TL(0, 2);
        mbar_wait(barStat, 0);
        if (tid == 0) TL(0, 3);
        named_bar<1, 256>();

        const float* scs = (const float*)(smem + K1_OFF_CS);
        const float2* srs = (const float2*)(smem + K1_OFF_RS);
        const int r0 = wg * 64 + w4 * 16 + g;
        const float2 st0 = srs[r0], st1 = srs[r0 + 8];
        const int grp0 = wg * 8 + w4 * 2;
        const bool poly0 = (POLYMASK >> grp0) & 1, poly1 = (POLYMASK >> (grp0 + 1)) & 1;
        const int mi = lane >> 3, mr = lane & 7;
        const uint32_t aMain = sb + (grp0 + (mi & 1)) * 384 + (mi >> 1) * 128 + mr * 16;
        const uint32_t aC2 = sb + (grp0 + (mi & 1)) * 384 + 256 + (mi >> 1) * 6144 + mr * 16;
        const uint32_t kx0 = (t & 1) ? (poly0 ? KAUX1 : 0u) : (poly0 ? KAUX0 : 0x3F80u), kx1 = (t & 1) ? (poly1 ? KAUX1 : 0u) : (poly1 ? KAUX0 : 0x3F80u);
        const uint32_t vx0 = (t & 1) ? 0u : (poly0 ? 0xBF80u : 0x3F80u), vx1 = (t & 1) ? 0u : (poly1 ? 0xBF80u : 0x3F80u);
        #define K1_PAIR(P) do { \
            const int G = nt * 12 + 2 * P, type = G >> 5; \
            float ra = st0.y, rb = st1.y; \
            uint32_t x0 = 0, x1 = 0; \
            if (type == 0) { ra *= QSCALE; rb *= QSCALE; } \
            if (type == 1) { x0 = kx0; x1 = kx1; } \
            if (type == 2) { if (poly0) ra = -ra; if (poly1) rb = -rb; x0 = vx0; x1 = vx1; } \
            const float ma = -st0.x * ra, mb = -st1.x * rb; \
            float v[5][4]; \
            uint32_t r[5][2]; \
            _Pragma("unroll") \
            for (int jm = 0; jm < 5; jm++) { \
                const int j = P * 5 + jm; \
                const float2 c = *(const float2*)(scs + 8 * j + 2 * t); \
                v[jm][0] = fmaf(acc[4 * j], ra, c.x * ma); v[jm][1] = fmaf(acc[4 * j + 1], ra, c.y * ma); \
                v[jm][2] = fmaf(acc[4 * j + 2], rb, c.x * mb); v[jm][3] = fmaf(acc[4 * j + 3], rb, c.y * mb); \
                r[jm][0] = pack_bf(v[jm][0], v[jm][1]); r[jm][1] = pack_bf(v[jm][2], v[jm][3]); \
            } \
            stmatrix_x4(aMain + P * 12288, r[0][0], r[0][1], r[1][0], r[1][1]); \
            stmatrix_x4(aMain + P * 12288 + 6144, r[3][0], r[3][1], r[4][0], r[4][1]); \
            stmatrix_x4(aC2 + P * 12288, t < 2 ? r[2][0] : x0, t < 2 ? r[2][1] : x1, t < 2 ? x0 : r[2][0], t < 2 ? x1 : r[2][1]); \
            fence_async_smem(); \
            named_arrive<5 + P, 288>(); \
            if (type == 1) { \
                float nA0, nA1, nB0, nB1; \
                nA0 = fmaf(v[0][0], v[0][0], fmaf(v[0][1], v[0][1], fmaf(v[1][0], v[1][0], v[1][1] * v[1][1]))); \
                nA1 = fmaf(v[0][2], v[0][2], fmaf(v[0][3], v[0][3], fmaf(v[1][2], v[1][2], v[1][3] * v[1][3]))); \
                nB0 = fmaf(v[3][0], v[3][0], fmaf(v[3][1], v[3][1], fmaf(v[4][0], v[4][0], v[4][1] * v[4][1]))); \
                nB1 = fmaf(v[3][2], v[3][2], fmaf(v[3][3], v[3][3], fmaf(v[4][2], v[4][2], v[4][3] * v[4][3]))); \
                const float q0 = fmaf(v[2][0], v[2][0], v[2][1] * v[2][1]), q1 = fmaf(v[2][2], v[2][2], v[2][3] * v[2][3]); \
                if (t < 2) { nA0 += q0; nA1 += q1; } else { nB0 += q0; nB1 += q1; } \
                nA0 += __shfl_xor_sync(~0u, nA0, 1); nA1 += __shfl_xor_sync(~0u, nA1, 1); \
                nB0 += __shfl_xor_sync(~0u, nB0, 1); nB1 += __shfl_xor_sync(~0u, nB1, 1); \
                nA0 += __shfl_xor_sync(~0u, nA0, 2); nA1 += __shfl_xor_sync(~0u, nA1, 2); \
                nB0 += __shfl_xor_sync(~0u, nB0, 2); nB1 += __shfl_xor_sync(~0u, nB1, 2); \
                  \
                const uint32_t mA = __reduce_max_sync(~0u, max(__float_as_uint(nA0), __float_as_uint(nA1))); \
                const uint32_t mB = __reduce_max_sync(~0u, max(__float_as_uint(nB0), __float_as_uint(nB1))); \
                if (lane == 0) { \
                    const int h = G & 31; \
                    g_kmax[h * 128 + mt * 8 + warp] = __uint_as_float(mA); \
                    g_kmax[(h + 1) * 128 + mt * 8 + warp] = __uint_as_float(mB); \
                } \
            } \
        } while (0)
        K1_PAIR(0); K1_PAIR(1); K1_PAIR(2); K1_PAIR(3); K1_PAIR(4); K1_PAIR(5);
        #undef K1_PAIR
        if (tid == 0) TL(0, 4);
    }
}

#define K2_UNR 2
#define K2_FIRST 2
constexpr int K2_OFF_BAR = 2 * HEAD_BYTES;
constexpr int K2_OFF_STG = K2_OFF_BAR + 256;
constexpr int K2_SMEM = K2_OFF_STG + 24576;

__device__ __forceinline__ float ex2(float y) { float e; asm("ex2.approx.ftz.f32 %0, %1;" : "=f"(e) : "f"(y)); return e; }
__device__ __forceinline__ uint32_t exp_pair_mufu(float y0, float y1) { return pack_bf(ex2(y0), ex2(y1)); }
__device__ __forceinline__ uint32_t hfma2(uint32_t a, uint32_t b, uint32_t c) {
    uint32_t r; asm("fma.rn.bf16x2 %0, %1, %2, %3;" : "=r"(r) : "r"(a), "r"(b), "r"(c)); return r;
}
__device__ __forceinline__ uint32_t exp_pair_poly(float y0, float y1, uint32_t cm, uint32_t ce) {
    const uint32_t G = __byte_perm(__float_as_uint(y0), __float_as_uint(y1), 0x6521);
    uint32_t w, z;
    asm("lop3.b32 %0, %1, %2, 0x3F003F00, 0xEA;" : "=r"(w) : "r"(G), "r"(cm));
    asm("lop3.b32 %0, %1, %2, 0x00030003, 0xEA;" : "=r"(z) : "r"(G), "r"(ce));
    return hfma2(G, w, z);
}
template<int MASK8>
__device__ __forceinline__ void softmax8(float (&s)[32], uint32_t (&p)[16], uint32_t cm, uint32_t ce) {
    #pragma unroll
    for (int i = 0; i < 32; i++) asm volatile("" : "+f"(s[i]) :: "memory");
    #pragma unroll
    for (int gi = 0; gi < 8; gi++) {
        if ((MASK8 >> gi) & 1) {
            p[2 * gi] = exp_pair_poly(s[4 * gi], s[4 * gi + 1], cm, ce);
            p[2 * gi + 1] = exp_pair_poly(s[4 * gi + 2], s[4 * gi + 3], cm, ce);
        } else {
            p[2 * gi] = exp_pair_mufu(s[4 * gi], s[4 * gi + 1]);
            p[2 * gi + 1] = exp_pair_mufu(s[4 * gi + 2], s[4 * gi + 3]);
        }
    }
}
__device__ __forceinline__ void attn_store(float (&o)[12], int row0, int head, int lane) {
    const int t = lane & 3, odd = head & 1;
    const int src = (lane & ~3) | (odd ? 0 : 2);
    const float l0 = __shfl_sync(~0u, o[8], src), l1 = __shfl_sync(~0u, o[10], src);
    const float r0 = __fdividef(1.f, l0), r1 = __fdividef(1.f, l1);
    bf16* o0 = g_o + (size_t)row0 * D_ + head * 20 + 2 * t;
    bf16* o1 = o0 + 8 * D_;
    const int c0 = odd ? 4 : 0, c2 = odd ? -4 : 16;
    *(uint32_t*)(o0 + c0) = pack_bf(o[0] * r0, o[1] * r0);
    *(uint32_t*)(o1 + c0) = pack_bf(o[2] * r1, o[3] * r1);
    *(uint32_t*)(o0 + c0 + 8) = pack_bf(o[4] * r0, o[5] * r0);
    *(uint32_t*)(o1 + c0 + 8) = pack_bf(o[6] * r1, o[7] * r1);
    if ((t < 2) != (bool)odd) {
        *(uint32_t*)(o0 + c2) = pack_bf(o[8] * r0, o[9] * r0);
        *(uint32_t*)(o1 + c2) = pack_bf(o[10] * r1, o[11] * r1);
    }
}

__device__ __forceinline__ void load_q(uint32_t sQ, int mt, uint32_t (&q)[8]) {
    const int lane = threadIdx.x & 31;
    const uint32_t base = sQ + ((threadIdx.x >> 7) * 16 + mt * 8 + ((threadIdx.x >> 5) & 3) * 2 + ((lane >> 3) & 1)) * 384 + (lane & 7) * 16;
    asm volatile("ldmatrix.sync.aligned.m8n8.x4.shared.b16 {%0,%1,%2,%3}, [%4];" : "=r"(q[0]), "=r"(q[1]), "=r"(q[2]), "=r"(q[3]) : "r"(base + (lane >> 4) * 128) : "memory");
    asm volatile("ldmatrix.sync.aligned.m8n8.x4.shared.b16 {%0,%1,%2,%3}, [%4];" : "=r"(q[4]), "=r"(q[5]), "=r"(q[6]), "=r"(q[7])
                 : "r"(lane < 16 ? base + 256 : sQ - K2_OFF_STG + K2_OFF_BAR + 128) : "memory");
}
__device__ __forceinline__ uint32_t patch_q(uint32_t (&q)[8], float km2, bool isaux, int t) {
    uint32_t unsafe = 0;
    #pragma unroll
    for (int r = 0; r < 2; r++) {
        float n2 = 0;
        #pragma unroll
        for (int i = 0; i < 3; i++) {
            const float lo = bf_lo(q[2 * i + r]), hi = bf_hi(q[2 * i + r]);
            n2 = fmaf(lo, lo, fmaf(hi, hi, n2));
        }
        n2 += __shfl_xor_sync(~0u, n2, 1);
        n2 += __shfl_xor_sync(~0u, n2, 2);
        float rt; asm("sqrt.approx.f32 %0, %1;" : "=f"(rt) : "f"(n2 * km2));
        const float B = rt * 1.01f + 0.01f;
        unsafe |= !(B <= 47.25f);
        const uint32_t nb = ((__float_as_uint(B) + 0xffffu) >> 16) | 0x8000u;
        if (isaux) q[4 + r] = (t & 1) ? 0x3F803F80u : (nb | 0x3F800000u);
    }
    return unsafe;
}
__device__ __forceinline__ uint32_t wg_any(uint32_t v, int wg) {
    asm volatile("{\n.reg .pred p, q;\nsetp.ne.u32 q, %0, 0;\nbar.red.or.pred p, %1, 128, q;\nselp.u32 %0, 1, 0, p;\n}\n" : "+r"(v) : "r"(1 + wg) : "memory");
    return v;
}
__device__ __forceinline__ void attn_safe(uint32_t sK, uint32_t sV, uint32_t sBar, const uint32_t (&q0)[8], int rowbase, int head) {
    const int tid = threadIdx.x, lane = tid & 31, t = lane & 3;
    const bool isaux = (t < 2) == (bool)(head & 1);
    for (int j = 0; j < 9; j++) mbar_wait(sBar + j * 8, 0);
    uint32_t q1[8];
    load_q(sK + K2_OFF_STG, 1, q1);
    #pragma unroll 1
    for (int mt = 0; mt < 2; mt++) {
        uint4 qa = mt ? make_uint4(q1[0], q1[1], q1[2], q1[3]) : make_uint4(q0[0], q0[1], q0[2], q0[3]);
        uint4 qb = mt ? make_uint4(q1[4], q1[5], 0, 0) : make_uint4(q0[4], q0[5], 0, 0);
        if (isaux) { qb.x = 0; qb.y = 0; }
        float o[12], s[32];
        uint32_t p[16];
        #pragma unroll
        for (int i = 0; i < 12; i++) { o[i] = 0.f; asm volatile("" : "+f"(o[i]) :: "memory"); }
        float m0 = -INFINITY, m1 = -INFINITY;
        #pragma unroll 1
        for (int u = 0; u < 32; u++) {
            const uint32_t kb = (((sK + u * 3072) & 0x3FFFF) >> 4) + (8u << 16), vb = (((sV + u * 3072) & 0x3FFFF) >> 4) + (24u << 16);
            wg_fence();
            mma_n64_rs<0>(s, qa.x, qa.y, qa.z, qa.w, make_desc(kb, 24));
            mma_n64_rs<1>(s, qb.x, qb.y, qb.z, qb.w, make_desc(kb + 16, 24));
            wg_commit();
            wg_wait<0>();
            #pragma unroll
            for (int i = 0; i < 32; i++) asm volatile("" : "+f"(s[i]) :: "memory");
            float n0 = m0, n1 = m1;
            #pragma unroll
            for (int gi = 0; gi < 8; gi++) {
                n0 = fmaxf(n0, fmaxf(s[4 * gi], s[4 * gi + 1]));
                n1 = fmaxf(n1, fmaxf(s[4 * gi + 2], s[4 * gi + 3]));
            }
            n0 = fmaxf(n0, __shfl_xor_sync(~0u, n0, 1)); n0 = fmaxf(n0, __shfl_xor_sync(~0u, n0, 2));
            n1 = fmaxf(n1, __shfl_xor_sync(~0u, n1, 1)); n1 = fmaxf(n1, __shfl_xor_sync(~0u, n1, 2));
            const float a0 = ex2(m0 - n0), a1 = ex2(m1 - n1);
            m0 = n0; m1 = n1;
            #pragma unroll
            for (int c = 0; c < 3; c++) { o[4 * c] *= a0; o[4 * c + 1] *= a0; o[4 * c + 2] *= a1; o[4 * c + 3] *= a1; }
            const uint32_t mask8 = (POLYMASK >> ((u & 1) * 8)) & 0xFF;
            #pragma unroll
            for (int gi = 0; gi < 8; gi++) {
                const uint32_t sg = ((mask8 >> gi) & 1) ? 0x80008000u : 0u;
                p[2 * gi] = pack_bf(ex2(s[4 * gi] - m0), ex2(s[4 * gi + 1] - m0)) ^ sg;
                p[2 * gi + 1] = pack_bf(ex2(s[4 * gi + 2] - m1), ex2(s[4 * gi + 3] - m1)) ^ sg;
            }
            #pragma unroll
            for (int i = 0; i < 12; i++) asm volatile("" : "+f"(o[i]) :: "memory");
            wg_fence();
            mma_n24_rs<1>(o, p[0], p[1], p[2], p[3], make_desc(vb, 8));
            mma_n24_rs<1>(o, p[4], p[5], p[6], p[7], make_desc(vb + 48, 8));
            mma_n24_rs<1>(o, p[8], p[9], p[10], p[11], make_desc(vb + 96, 8));
            mma_n24_rs<1>(o, p[12], p[13], p[14], p[15], make_desc(vb + 144, 8));
            wg_commit();
            wg_wait<0>();
            #pragma unroll
            for (int i = 0; i < 12; i++) asm volatile("" : "+f"(o[i]) :: "memory");
        }
        attn_store(o, rowbase + mt * 64, head, lane);
    }
}

constexpr int K2_MOVERS = 4;
constexpr int WIMG_DOWN = 96 * 40960;
__device__ __forceinline__ void k2_mover(const CUtensorMap* tmG, const CUtensorMap* tmU, const CUtensorMap* tmD, uint32_t sb) {
    const int tid = threadIdx.x, warp = tid >> 5, lane = tid & 31;
    constexpr int NS = 6, NQ = 3;
    const uint32_t sOut = sb + NS * 24576, barFull = sOut + NQ * 24576, barEmpty = barFull + 8 * NS, barOut = barEmpty + 8 * NS, barFree = barOut + 8 * NQ;
    constexpr int NI = (192 + 80) / K2_MOVERS;
    if (tid == 0) {
        TL(4, 5);
        for (int i = 0; i < NS; i++) { mbar_init(barFull + 8 * i, 1); mbar_init(barEmpty + 8 * i, 12); }
        for (int i = 0; i < NQ; i++) { mbar_init(barOut + 8 * i, 12); mbar_init(barFree + 8 * i, 1); }
        fence_mbar_init();
        fence_async_smem();
    }
    __syncthreads();
    if (warp == 0) {
        if (lane == 0) {
            uint64_t pol;
            asm volatile("createpolicy.fractional.L2::evict_first.b64 %0, 1.0;" : "=l"(pol));
            int s = 0, ph = 1;
            #pragma unroll 1
            for (int n = 0; n < NI; n++) {
                const int id = n * K2_MOVERS + blockIdx.x;
                if (n >= NS) mbar_wait(barEmpty + 8 * s, ph);
                const bool gu = id < 192;
                const CUtensorMap* tm = gu ? (id < 96 ? tmG : tmU) : tmD;
                const int c0 = gu ? ((id % 96) >> 2) * 64 : ((id - 192) >> 3) * 64, c1 = gu ? (id & 3) * 160 : (id & 7) * 192;
                mbar_expect_tx(barFull + 8 * s, gu ? 20480 : 24576);
                asm volatile("cp.async.bulk.tensor.2d.shared::cluster.global.mbarrier::complete_tx::bytes.L2::cache_hint [%0], [%1, {%3, %4}], [%2], %5;"
                    :: "r"(sb + s * 24576), "l"(tm), "r"(barFull + 8 * s), "r"(c0), "r"(c1), "l"(pol) : "memory");
                if (++s == NS) { s = 0; ph ^= 1; }
            }
        }
    } else if (warp == 13) {
        if (lane == 0) {
            int q = 0, ph = 0;
            #pragma unroll 1
            for (int n = 0; n < NI; n++) {
                const int id = n * K2_MOVERS + blockIdx.x;
                const bool gu = id < 192;
                const int u = gu ? (id >= 96 ? id - 96 : id) : id - 192;
                const uint32_t len = gu ? 5120 : 6144;
                uint8_t* dst = g_wimg + (gu ? ((u >> 2) * 32 + (id >= 96 ? 4 : 0) + (u & 3)) * 5120 : WIMG_DOWN + ((u >> 3) * 32 + (u & 7)) * 6144);
                mbar_wait(barOut + 8 * q, ph);
                for (int bl = 0; bl < 4; bl++) bulk_s2g(dst + bl * 8 * len, sOut + q * 24576 + bl * 6144, len);
                bulk_commit();
                asm volatile("cp.async.bulk.wait_group.read 1;" ::: "memory");
                if (n > 0) mbar_arrive(barFree + 8 * (q == 0 ? NQ - 1 : q - 1));
                if (++q == NQ) { q = 0; ph ^= 1; }
            }
            bulk_wait_all();
            TL(4, 6);
        }
    } else if (warp <= 12) {
        const int g = lane >> 2, t = lane & 3, m = (warp - 1) >> 1, h = (warp - 1) & 1;
        const int row = m * 32 + (((g >> 1) & 1) * 4 + t) * 2 + (g >> 2) * 16;
        const uint32_t src = sb + row * 128, sw = (row & 7) ^ (g & 1), dst = sOut + h * 2 * 6144 + m * 1024 + lane * 16;
        int s = 0, ph = 0, q = 0, qh = 1;
        #pragma unroll 1
        for (int n = 0; n < NI; n++) {
            const bool on = n * K2_MOVERS + blockIdx.x >= 192 || m < 5;
            mbar_wait(barFull + 8 * s, ph);
            uint4 u[2], v[2];
            if (on) {
                #pragma unroll
                for (int bl = 0; bl < 2; bl++) {
                    u[bl] = lds_v4(src + s * 24576 + (((h * 4 + bl * 2) ^ sw) << 4));
                    v[bl] = lds_v4(src + 128 + s * 24576 + (((h * 4 + bl * 2) ^ sw ^ 1) << 4));
                }
            }
            if (n >= NQ) mbar_wait(barFree + 8 * q, qh);
            if (on) {
                #pragma unroll
                for (int bl = 0; bl < 2; bl++) {
                    sts_v4(dst + q * 24576 + bl * 6144, make_uint4(u[bl].x, v[bl].x, u[bl].y, v[bl].y));
                    sts_v4(dst + q * 24576 + bl * 6144 + 512, make_uint4(u[bl].z, v[bl].z, u[bl].w, v[bl].w));
                }
            }
            fence_async_smem();
            __syncwarp();
            if (lane == 0) { mbar_arrive(barEmpty + 8 * s); mbar_arrive(barOut + 8 * q); }
            if (++s == NS) { s = 0; ph ^= 1; }
            if (++q == NQ) { q = 0; qh ^= 1; }
        }
    }
}

static_assert((POLYMASK & 0xFF) == (POLYMASK >> 8), "both 64-key tiles of a 128-key block use the same pattern");

__global__ void __launch_bounds__(512, 1)
k2_attn(const __grid_constant__ CUtensorMap tmG, const __grid_constant__ CUtensorMap tmU, const __grid_constant__ CUtensorMap tmD,
        uint32_t cm, uint32_t ce) {
    extern __shared__ __align__(1024) uint8_t smem[];
    if (blockIdx.x < K2_MOVERS) {
        k2_mover(&tmG, &tmU, &tmD, smem_u32(smem));
        return;
    }
    const int bid = blockIdx.x - K2_MOVERS;
    const int head = bid >> 2, quarter = bid & 3;
    const uint32_t sK = smem_u32(smem), sV = sK + HEAD_BYTES, sBar = sK + K2_OFF_BAR, sStg = sK + K2_OFF_STG;
    const int tid = threadIdx.x, wg = tid >> 7, warp = (tid >> 5) & 3, lane = tid & 31, g = lane >> 2, t = lane & 3;
    if (tid == 0) TL(1, 0);
    if (tid == 0) {
        for (int i = 0; i < 9; i++) mbar_init(sBar + i * 8, 1);
        fence_mbar_init();
        fence_async_smem();
        for (int i = 0; i < 4; i++) mbar_expect_tx(sBar + i * 8, 12288);
        mbar_expect_tx(sBar + 32, 4 * 12288);
        mbar_expect_tx(sBar + 40, 12288);
        mbar_expect_tx(sBar + 48, 12288);
        mbar_expect_tx(sBar + 56, 4 * 12288);
        mbar_expect_tx(sBar + 64, 4 * 12288);
    }
    if (tid == 32) sts_v4(sBar + 128, make_uint4(0, 0, 0, 0));
    if (tid >= 64 && tid < 64 + 148) *(uint4*)(g_xc + (bid * 148 + tid - 64) * 16) = make_uint4(~0u, ~0u, ~0u, ~0u);
    __syncthreads();
    pdl_wait();
    pdl_launch();
    if (tid == 0) TL(1, 1);
    const uint8_t* Qp = g_qkv + (size_t)head * HEAD_BYTES + (quarter * 64 + wg * 16) * 384;
    const uint8_t* Kp = g_qkv + (size_t)(32 + head) * HEAD_BYTES;
    const uint8_t* Vp = g_qkv + (size_t)(64 + head) * HEAD_BYTES;
    const float4 k4 = __ldcg((const float4*)(g_kmax + head * 128) + lane);
    if (lane == 0) {
        if (warp == 0) bulk_g2s(sStg + wg * 6144, Qp, 3072, sBar + 40);
        const int c = wg * 3 + warp - 1;
        if (warp > 0 && c < K2_FIRST) {
            bulk_g2s(sK + c * 6144, Kp + c * 6144, 6144, sBar + c * 8);
            bulk_g2s(sV + c * 6144, Vp + c * 6144, 6144, sBar + c * 8);
        }
    }
    if (tid == 0) TL(1, 20);
    float km2;
    {
        const uint32_t m = max(max(__float_as_uint(k4.x), __float_as_uint(k4.y)), max(__float_as_uint(k4.z), __float_as_uint(k4.w)));
        km2 = __uint_as_float(__reduce_max_sync(~0u, m));
    }
    if (tid == 0 && km2 >= 0.f) TL(1, 21);
    const int rowbase = quarter * 512 + wg * 128 + warp * 16 + g;
    const bool isaux = (t < 2) == (bool)(head & 1);
    uint32_t q0[8], q1[8];
    mbar_wait(sBar + 40, 0);
    if (tid == 0) TL(1, 17);
    if (lane == 0 && warp == 1 && wg >= K2_FIRST) {
        bulk_g2s(sK + wg * 6144, Kp + wg * 6144, 6144, sBar + wg * 8);
        bulk_g2s(sV + wg * 6144, Vp + wg * 6144, 6144, sBar + wg * 8);
    }
    load_q(sStg, 0, q0);
    uint32_t unsafe = patch_q(q0, km2, isaux, t);
    unsafe = wg_any(unsafe, wg);
    if (tid == 0) TL(1, 16);

    #define GROUP_LOAD(G) do { if (lane == 0 && warp == 2 && wg == (G) + 1) { const uint32_t bar = sBar + ((G) == 0 ? 32 : 48 + 8 * (G)); \
        bulk_g2s(sK + wg * 4 * 6144, Kp + wg * 4 * 6144, 4 * 6144, bar); bulk_g2s(sV + wg * 4 * 6144, Vp + wg * 4 * 6144, 4 * 6144, bar); } } while (0)
    #define Q1_LOAD() do { if (lane == 0 && warp == 3) bulk_g2s(sStg + wg * 6144 + 3072, Qp + 3072, 3072, sBar + 48); } while (0)
    float s[32];
    float o[12];
    uint32_t p[16];
    uint4 qa = make_uint4(q0[0], q0[1], q0[2], q0[3]), qb = make_uint4(q0[4], q0[5], q0[6], q0[7]);
    uint64_t dk, dv;
    #define SET_DESC(KT, VT) do { uint32_t b_; asm volatile("mov.u32 %0, smem;" : "=r"(b_)); \
        dk = make_desc((b_ >> 4) + (KT) * 192 + (8u << 16), 24); dv = make_desc(((b_ + HEAD_BYTES) >> 4) + (VT) * 192 + (24u << 16), 8); } while (0)
    #define ISSUE_QK() do { mma_n64_rs<0>(s, qa.x, qa.y, qa.z, qa.w, dk); mma_n64_rs<1>(s, qb.x, qb.y, qb.z, qb.w, dk + 16); dk += 192; } while (0)
    #define PV(SD) do { mma_n24_rs<SD>(o, p[0], p[1], p[2], p[3], dv); mma_n24_rs<1>(o, p[4], p[5], p[6], p[7], dv + 48); \
                      mma_n24_rs<1>(o, p[8], p[9], p[10], p[11], dv + 96); mma_n24_rs<1>(o, p[12], p[13], p[14], p[15], dv + 144); dv += 192; } while (0)
    constexpr int MA = POLYMASK & 0xFF;
    #define STEP(SD) do { wg_wait<0>(); softmax8<MA>(s, p, cm, ce); wg_fence(); PV(SD); ISSUE_QK(); wg_commit(); } while (0)
    if (!__any_sync(~0u, unsafe)) {
        mbar_wait_warp(sBar, 0);
        if (tid == 0) { TL(1, 2); TLC(1, 5); }
        SET_DESC(0, 0);
        wg_fence();
        ISSUE_QK();
        wg_commit();
        GROUP_LOAD(0);
        Q1_LOAD();
        STEP(0);
        SET_DESC(2, 1);
        #pragma unroll 1
        for (int j = 1; j < 4; j++) {
            mbar_wait_warp(sBar + j * 8, 0);
            STEP(1); STEP(1);
        }
        GROUP_LOAD(1);
        GROUP_LOAD(2);
        if (tid == 0) TLC(1, 18);
        mbar_wait_warp(sBar + 48, 0);
        load_q(sStg, 1, q1);
        unsafe = wg_any(patch_q(q1, km2, isaux, t), wg);
    }
    else { GROUP_LOAD(0); Q1_LOAD(); GROUP_LOAD(1); GROUP_LOAD(2); }
    if (__any_sync(~0u, unsafe)) {
        wg_wait<0>();
        #pragma unroll
        for (int i = 0; i < 32; i++) asm volatile("" : "+f"(s[i]) :: "memory");
        #pragma unroll
        for (int i = 0; i < 12; i++) asm volatile("" : "+f"(o[i]) :: "memory");
        attn_safe(sK, sV, sBar, q0, rowbase, head);
        return;
    }
    #pragma unroll 1
    for (int c = 0; c < 3; c++) {
        mbar_wait_warp(sBar + (c == 0 ? 32 : 48 + 8 * c), 0);
        if (tid == 0 && c == 0) TLC(1, 19);
        SET_DESC(8 + 8 * c, 7 + 8 * c);
        #pragma unroll 1
        for (int j = 0; j < 8 / K2_UNR; j++) { STEP(1); if (K2_UNR > 1) STEP(1); }
    }
    wg_wait<0>();
    qa = make_uint4(q1[0], q1[1], q1[2], q1[3]); qb = make_uint4(q1[4], q1[5], q1[6], q1[7]);
    softmax8<MA>(s, p, cm, ce);
    SET_DESC(0, 31);
    wg_fence();
    PV(1);
    ISSUE_QK();
    wg_commit();
    wg_wait<0>();
    #pragma unroll
    for (int i = 0; i < 12; i++) asm volatile("" : "+f"(o[i]) :: "memory");
    attn_store(o, rowbase, head, lane);
    if ((tid & 127) == 0) TL(1, 8 + wg);
    if (tid == 0) { TL(1, 3); TLC(1, 6); }
    SET_DESC(1, 0);
    STEP(0);
    SET_DESC(2, 1);
    #pragma unroll 1
    for (int j = 0; j < 30 / K2_UNR; j++) { STEP(1); if (K2_UNR > 1) STEP(1); }
    wg_wait<0>();
    softmax8<MA>(s, p, cm, ce);
    SET_DESC(0, 31);
    wg_fence();
    PV(1);
    wg_commit();
    wg_wait<0>();
    #pragma unroll
    for (int i = 0; i < 12; i++) asm volatile("" : "+f"(o[i]) :: "memory");
    attn_store(o, rowbase + 64, head, lane);
    if ((tid & 127) == 0) TL(1, 12 + wg);
    if (tid == 0) { TL(1, 4); TLC(1, 7); }
    #undef SET_DESC
    #undef GROUP_LOAD
    #undef Q1_LOAD
    #undef STEP
    #undef PV
    #undef ISSUE_QK
}

#define K3_WKT 8
#define K3_NPRE 2
constexpr int K3_NB = 7;
constexpr int K3_BT = 20480;
constexpr int K3_OFF_B = 10 * 8192;
constexpr int K3_OFF_BAR = K3_OFF_B + K3_NB * K3_BT;
constexpr int K3_OFF_TOP = K3_OFF_BAR + 256;
constexpr int K3_OFF_SEL = K3_OFF_TOP + 512;
constexpr int K3_OFF_RED = K3_OFF_SEL + 16;
constexpr int K3_OFF_HL = K3_OFF_RED + 1024;
constexpr int K3_XS = 1344, K3_HS = 3136;
constexpr int K3_OFF_X = K3_OFF_HL + 128;
constexpr int K3_SMEM = K3_OFF_X + 2 * K3_XS;
constexpr int K3_OFF_WG = K3_OFF_B + 3 * K3_BT, K3_OFF_WD = 0, K3_OFF_HF = 6 * 8192;

__device__ __forceinline__ uint32_t order_key(float v) {
    const uint32_t u = __float_as_uint(v);
    return u ^ (((int)u >> 31) | 0x80000000u);
}
__device__ __forceinline__ uint32_t row_key(float score, int row) { return (min(order_key(score), 0xFFFFEFFFu) & 0xFFFFF000u) | ((S_ - 1 - row) << 1); }
__device__ __forceinline__ int key_row(uint32_t k) { return S_ - 1 - ((k >> 1) & (S_ - 1)); }
__device__ __forceinline__ void warp_top2(uint32_t& k0, uint32_t& k1) {
    const uint32_t m0 = __reduce_max_sync(~0u, k0);
    k1 = __reduce_max_sync(~0u, k0 == m0 ? k1 : k0);
    k0 = m0;
}
__device__ __forceinline__ uint4 ldx_v4(const void* p) {
    uint4 v; asm volatile("ld.relaxed.gpu.global.v4.b32 {%0,%1,%2,%3}, [%4];" : "=r"(v.x), "=r"(v.y), "=r"(v.z), "=r"(v.w) : "l"(p) : "memory"); return v;
}
__device__ __forceinline__ void stx_v4(void* p, uint32_t a, uint32_t b, uint32_t c, uint32_t d, bool on) {
    asm volatile("{\n.reg .pred p;\nsetp.ne.u32 p, %5, 0;\n@p st.relaxed.gpu.global.v4.b32 [%0], {%1,%2,%3,%4};\n}\n"
        :: "l"(p), "r"(a), "r"(b), "r"(c), "r"(d), "r"((uint32_t)on) : "memory");
}
__device__ __forceinline__ void st_v4(void* p, uint32_t a, uint32_t b, uint32_t c, uint32_t d, bool on) {
    asm volatile("{\n.reg .pred p;\nsetp.ne.u32 p, %5, 0;\n@p st.global.v4.b32 [%0], {%1,%2,%3,%4};\n}\n"
        :: "l"(p), "r"(a), "r"(b), "r"(c), "r"(d), "r"((uint32_t)on) : "memory");
}
__device__ __forceinline__ bool valid4(const uint4 v) { return v.x != ~0u && v.y != ~0u && v.z != ~0u && v.w != ~0u; }
template<int NL>
__device__ __forceinline__ void poll(const uint8_t* p, uint32_t stride, uint4 (&r)[NL]) {
    uint32_t it = 0;
    bool ok;
    do {
        ok = true;
        #pragma unroll
        for (int l = 0; l < NL; l++) r[l] = ldx_v4(p + l * stride);
        #pragma unroll
        for (int l = 0; l < NL; l++) ok = ok && valid4(r[l]);
        if (++it > (1u << 22)) __trap();
    } while (!__all_sync(~0u, ok));
}
__device__ __forceinline__ uint32_t lds_flag(uint32_t a) { uint32_t v; asm volatile("ld.acquire.cta.shared.b32 %0, [%1];" : "=r"(v) : "r"(a) : "memory"); return v; }
__device__ __forceinline__ void sts_flag(uint32_t a) { asm volatile("st.release.cta.shared.b32 [%0], %1;" :: "r"(a), "r"(1) : "memory"); }
__device__ __forceinline__ void wait_flag(uint32_t a) { uint32_t it = 0; while (!lds_flag(a)) { if (++it > (1u << 26)) __trap(); } }
__device__ __forceinline__ void pause(uint32_t cycles) { const uint32_t c0 = clock(); while (clock() - c0 < cycles) {} }
#define K3_EARLY 0
#define K3_PACE 100
#define K3_PACE0 500
#define K3_KPOLL 1
#define K3_KGAP 270
__device__ __forceinline__ uint32_t hadd_bf2(uint32_t a, uint32_t b) {
    uint32_t r; asm("add.rn.bf16x2 %0, %1, %2;" : "=r"(r) : "r"(a), "r"(b)); return r;
}
template<int NB>
__device__ __forceinline__ void gemv16(const uint4 (&w)[2 * NB], uint32_t xs, uint32_t pitch, float* red, int lane) {
    const int g = lane >> 2, t = lane & 3;
    const uint32_t xa = xs + ((g >> 1) & 1) * pitch + ((g >> 2) * 4 + t) * 4;
    const uint32_t selLo = (g & 1) ? 0x1044u : 0x4410u, selHi = (g & 1) ? 0x3244u : 0x4432u;
    float c[4][4];
    #pragma unroll
    for (int j = 0; j < 4; j++) { c[j][0] = 0.f; c[j][1] = 0.f; c[j][2] = 0.f; c[j][3] = 0.f; }
    uint32_t x0[NB], x1[NB];
    #pragma unroll
    for (int i = 0; i < NB; i++) {
        asm volatile("ld.shared.b32 %0, [%1];" : "=r"(x0[i]) : "r"(xa + 64 * i) : "memory");
        asm volatile("ld.shared.b32 %0, [%1];" : "=r"(x1[i]) : "r"(xa + 64 * i + 32) : "memory");
    }
    #pragma unroll
    for (int i = 0; i < NB; i++) {
        const uint32_t a0 = __byte_perm(x0[i], 0, selLo), a2 = __byte_perm(x0[i], 0, selHi), a1 = __byte_perm(x1[i], 0, selLo), a3 = __byte_perm(x1[i], 0, selHi);
        const uint32_t b0[4] = {w[2 * i].x, w[2 * i].z, w[2 * i + 1].x, w[2 * i + 1].z}, b1[4] = {w[2 * i].y, w[2 * i].w, w[2 * i + 1].y, w[2 * i + 1].w};
        #pragma unroll
        for (int j = 0; j < 4; j++)
            asm volatile("mma.sync.aligned.m16n8k16.row.col.f32.bf16.bf16.f32 {%0,%1,%2,%3}, {%4,%5,%6,%7}, {%8,%9}, {%0,%1,%2,%3};"
                : "+f"(c[j][0]), "+f"(c[j][1]), "+f"(c[j][2]), "+f"(c[j][3]) : "r"(a0), "r"(a1), "r"(a2), "r"(a3), "r"(b0[j]), "r"(b1[j]));
    }
    float v[4];
    #pragma unroll
    for (int j = 0; j < 4; j++) {
        const float keep = t < 2 ? c[j][0] : c[j][3], send = t < 2 ? c[j][1] : c[j][2];
        v[j] = keep + __shfl_xor_sync(~0u, send, 2);
    }
    const bool odd = t & 1;
    const float e0 = (odd ? v[2] : v[0]) + __shfl_xor_sync(~0u, odd ? v[0] : v[2], 17);
    const float e1 = (odd ? v[3] : v[1]) + __shfl_xor_sync(~0u, odd ? v[1] : v[3], 17);
    if ((t & 1) == (g >> 2)) {
        float* r = red + (((g >> 1) & 1) * 16 + (t >> 1) * 8 + (t & 1) * 4 + (g & 1)) * 8;
        r[0] = e0; r[16] = e1;
    }
}

__global__ void __launch_bounds__(384, 1)
k3_tail(const __grid_constant__ CUtensorMap tmO, const __grid_constant__ CUtensorMap tmR, const bf16* __restrict__ wr, bf16* __restrict__ out) {
    extern __shared__ __align__(1024) uint8_t smem[];
    const uint32_t sb = smem_u32(smem);
    uint32_t barFull = sb + K3_OFF_BAR;
    const int tid = threadIdx.x, warp = tid >> 5, lane = tid & 31, b = blockIdx.x;
    const int nt = b & 3, mt = b >> 2;
    const int g = lane >> 2, t = lane & 3;
    if (warp < 4) {
        float acc[80], wv[40], wsum;
        cluster_arrive();
        const uint32_t hiA = 64u | (1u << 30), hiB = 8u;
        const uint32_t sa = __reduce_max_sync(~0u, (sb & 0x3FFFF) >> 4);
        uint4 xa[5], xb[5], wp[5];
        if (tid == 0) TL(2, 7);
        cluster_wait();
        mbar_wait_warp(barFull + 120, 0);
        #pragma unroll
        for (int J = 0; J < 5; J++) {
            const uint32_t xs = sb + K3_OFF_B + (K3_NB - 1) * K3_BT + (warp * 16 + g) * 320 + 16 * t + 64 * J;
            xa[J] = lds_v4(xs); xb[J] = lds_v4(xs + 8 * 320); wp[J] = lds_v4(sb + K3_OFF_RED + 16 * t + 64 * J);
        }
        wsum = 0.f;
        #pragma unroll
        for (int J = 0; J < 5; J++) {
            const uint32_t xw0[4] = {xa[J].x, xa[J].y, xa[J].z, xa[J].w}, xw1[4] = {xb[J].x, xb[J].y, xb[J].z, xb[J].w};
            const uint32_t ww[4] = {wp[J].x, wp[J].y, wp[J].z, wp[J].w};
            #pragma unroll
            for (int jj = 0; jj < 4; jj++) {
                const int j = 4 * J + jj;
                acc[4 * j] = bf_lo(xw0[jj]); acc[4 * j + 1] = bf_hi(xw0[jj]); acc[4 * j + 2] = bf_lo(xw1[jj]); acc[4 * j + 3] = bf_hi(xw1[jj]);
                wv[2 * j] = bf_lo(ww[jj]); wv[2 * j + 1] = bf_hi(ww[jj]);
                wsum += wv[2 * j] + wv[2 * j + 1];
            }
        }
        wsum += __shfl_xor_sync(~0u, wsum, 1);
        wsum += __shfl_xor_sync(~0u, wsum, 2);
        asm volatile("" : "+f"(wsum));
        #pragma unroll
        for (int i = 0; i < 40; i++) asm volatile("" : "+f"(wv[i]));
        #pragma unroll
        for (int i = 0; i < 80; i++) asm volatile("" : "+f"(acc[i]) :: "memory");
        asm volatile("" : "+r"(barFull));
        if (lane == 0) mbar_arrive(barFull + 128);
        pdl_wait();
        #pragma unroll 1
        for (int kt = 0; kt < 10; kt++) {
            mbar_wait_warp(barFull + 8 * kt, 0);
            if (tid == 0 && kt == 0) TL(2, 2);
            const int slot = kt < K3_NB ? kt : kt - K3_NB;
            const uint32_t loA = sa + kt * 512 + (1u << 16), loB = sa + (K3_OFF_B >> 4) + slot * (K3_BT >> 4) + (160u << 16);
            wg_fence();
            #pragma unroll
            for (int kk = 0; kk < 4; kk++)
                mma_n160_ss(acc, make_desc(loA + 2 * kk, hiA), make_desc(loB + 320 * kk, hiB), 1);
            wg_commit();
            if (((0xE | (K3_WKT < 10 ? 1 << (K3_WKT - 1) : 0)) >> kt) & 1) {
                wg_wait<1>();
                if (lane == 0) mbar_arrive(barFull + 80 + 8 * min(kt - 1, 3));
            }
        }
        wg_wait<0>();
        if (K3_WKT == 10 && lane == 0) mbar_arrive(barFull + 104);
        #pragma unroll
        for (int i = 0; i < 80; i++) asm volatile("" : "+f"(acc[i]) :: "memory");
        if (tid == 0) { TL(2, 3); TLC(3, 16); }

        const int r0 = mt * 64 + warp * 16 + g;
        float s0 = 0.f, q0 = 0.f, d0 = 0.f, s1 = 0.f, q1 = 0.f, d1 = 0.f;
        #pragma unroll
        for (int j = 0; j < 20; j++) {
            const float a0 = acc[4 * j], a1 = acc[4 * j + 1], b0 = acc[4 * j + 2], b1 = acc[4 * j + 3];
            s0 += a0 + a1; q0 = fmaf(a0, a0, fmaf(a1, a1, q0)); d0 = fmaf(a0, wv[2 * j], fmaf(a1, wv[2 * j + 1], d0));
            s1 += b0 + b1; q1 = fmaf(b0, b0, fmaf(b1, b1, q1)); d1 = fmaf(b0, wv[2 * j], fmaf(b1, wv[2 * j + 1], d1));
        }
        #pragma unroll
        for (int o = 1; o < 4; o <<= 1) {
            s0 += __shfl_xor_sync(~0u, s0, o); q0 += __shfl_xor_sync(~0u, q0, o); d0 += __shfl_xor_sync(~0u, d0, o);
            s1 += __shfl_xor_sync(~0u, s1, o); q1 += __shfl_xor_sync(~0u, q1, o); d1 += __shfl_xor_sync(~0u, d1, o);
        }
        uint8_t* part = g_xc + XC_PART + r0 * 64;
        stx_v4(part + (t & 1) * 512 + nt * 16, __float_as_uint(t & 1 ? s1 : s0), __float_as_uint(t & 1 ? q1 : q0), __float_as_uint(t & 1 ? d1 : d0),
               __float_as_uint(wsum), t < 2);
        if (K3_WKT == 12 && lane == 0) mbar_arrive(barFull + 104);
        if (tid == 0) { TL(2, 4); TLC(3, 17); }
        uint4 pr[2];
        poll(part + t * 16, 512, pr);
        const uint4 ua = pr[0], ub = pr[1];
        if (K3_WKT == 11 && lane == 0) mbar_arrive(barFull + 104);
        if (tid == 0) { TL(2, 5); TLC(3, 18); }
        s0 = __uint_as_float(ua.x); q0 = __uint_as_float(ua.y); d0 = __uint_as_float(ua.z);
        s1 = __uint_as_float(ub.x); q1 = __uint_as_float(ub.y); d1 = __uint_as_float(ub.z);
        float ws = __uint_as_float(ua.w);
        #pragma unroll
        for (int o = 1; o < 4; o <<= 1) {
            s0 += __shfl_xor_sync(~0u, s0, o); q0 += __shfl_xor_sync(~0u, q0, o); d0 += __shfl_xor_sync(~0u, d0, o);
            s1 += __shfl_xor_sync(~0u, s1, o); q1 += __shfl_xor_sync(~0u, q1, o); d1 += __shfl_xor_sync(~0u, d1, o);
            ws += __shfl_xor_sync(~0u, ws, o);
        }
        const float mua = s0 * (1.f / D_), mub = s1 * (1.f / D_);
        const float rsa = rsqrtf(fmaxf(q0 * (1.f / D_) - mua * mua, 0.f) + 1e-5f), rsb = rsqrtf(fmaxf(q1 * (1.f / D_) - mub * mub, 0.f) + 1e-5f);
        uint2* s_top = (uint2*)(smem + K3_OFF_TOP);
        if (t < 2) {
            const float score = t == 0 ? rsa * (d0 - mua * ws) : rsb * (d1 - mub * ws);
            s_top[warp * 16 + g + 8 * t] = make_uint2(row_key(score, r0 + 8 * t), __float_as_uint(score));
        }
        if (tid == 0) TLC(3, 20);
        named_bar<3, 128>();
        if (tid == 0) TLC(3, 21);
        const uint4 tv = ((const uint4*)s_top)[lane];
        uint32_t k0 = max(tv.x, tv.z), k1 = min(tv.x, tv.z);
        warp_top2(k0, k1);
        const int i0 = key_row(k0), i1 = key_row(k1);
        if (tid == 0) {
            stx_v4(g_xc + XC_KEYS + nt * 512 + mt * 16, k0, k1 | 1, s_top[i0 & 63].y, s_top[i1 & 63].y, true);
            TL(2, 9); TLC(3, 22);
        }
        const bool ca = r0 == i0 || r0 == i1, cb = r0 + 8 == i0 || r0 + 8 == i1;
        uint8_t* cpa = g_xc + XC_CAND + (mt * 2 + (r0 == i1)) * 2560 + (nt * 160 + 8 * t) * 2;
        uint8_t* cpb = g_xc + XC_CAND + (mt * 2 + (r0 + 8 == i1)) * 2560 + (nt * 160 + 8 * t) * 2;
        bf16* o0 = out + (size_t)r0 * D_ + nt * 160 + 8 * t;
        const float ma = -mua * rsa, mb = -mub * rsb;
        uint32_t oa[20], ob[20];
        #pragma unroll
        for (int J = 0; J < 5; J++) {
            uint32_t ha[4], hb[4], la[4], lb[4];
            #pragma unroll
            for (int jj = 0; jj < 4; jj++) {
                const int j = 4 * J + jj;
                ha[jj] = pack_bf(acc[4 * j], acc[4 * j + 1]); hb[jj] = pack_bf(acc[4 * j + 2], acc[4 * j + 3]);
                la[jj] = pack_bf(fmaf(acc[4 * j], rsa, ma), fmaf(acc[4 * j + 1], rsa, ma));
                lb[jj] = pack_bf(fmaf(acc[4 * j + 2], rsb, mb), fmaf(acc[4 * j + 3], rsb, mb));
                oa[j] = hadd_bf2(ha[jj], la[jj]); ob[j] = hadd_bf2(hb[jj], lb[jj]);
            }
            stx_v4(cpa + 64 * J, la[0], la[1], la[2], la[3], ca);
            stx_v4(cpb + 64 * J, lb[0], lb[1], lb[2], lb[3], cb);
            stx_v4(cpa + 64 * J + 1280, ha[0], ha[1], ha[2], ha[3], ca);
            stx_v4(cpb + 64 * J + 1280, hb[0], hb[1], hb[2], hb[3], cb);
        }
        if (tid == 0) { TL(2, 8); TLC(3, 23); }
        wait_flag(barFull + 192);
        const uint2 sel = *(const uint2*)(smem + K3_OFF_SEL);
        const int row0 = key_row(sel.x), row1 = key_row(sel.y);
        const bool wa = (ca || !K3_EARLY) && r0 != row0 && r0 != row1, wb = (cb || !K3_EARLY) && r0 + 8 != row0 && r0 + 8 != row1;
        #pragma unroll
        for (int J = 0; J < 5; J++) {
            if (J ? K3_PACE : K3_PACE0) pause(J ? K3_PACE : K3_PACE0);
            st_v4(o0 + 32 * J, oa[4 * J], oa[4 * J + 1], oa[4 * J + 2], oa[4 * J + 3], wa);
            st_v4(o0 + 8 * D_ + 32 * J, ob[4 * J], ob[4 * J + 1], ob[4 * J + 2], ob[4 * J + 3], wb);
        }
        if (tid == 0) TL(2, 6);
        return;
    }
    if (warp == 11) {
        const uint8_t* img = g_wo_img + nt * (10 * K3_BT);
        const uint32_t barEmpty = barFull + 80;
        if (lane == 0) {
            TL(2, 0);
            tmap_prefetch(&tmO);
            for (int i = 0; i < 10; i++) mbar_init(barFull + 8 * i, 1);
            for (int i = 0; i < 4; i++) mbar_init(barEmpty + 8 * i, 4);
            mbar_init(barFull + 112, 1);
            mbar_init(barFull + 120, 1);
            mbar_init(barFull + 128, 4);
            asm volatile("st.shared.b32 [%0], %1;\nfence.acq_rel.cta;" :: "r"(barFull + 192), "r"(0) : "memory");
            fence_mbar_init();
            fence_async_smem();
            for (int i = 0; i < 10; i++) mbar_expect_tx(barFull + 8 * i, 8192 + K3_BT);
            mbar_expect_tx(barFull + 112, (b < 96 ? 40960 : 0) + (b >= 88 ? 49152 : 0));
            mbar_expect_tx(barFull + 120, K3_BT + 320);
            tma_2d(sb + K3_OFF_B + (K3_NB - 1) * K3_BT, &tmR, nt * 160, mt * 64, barFull + 120);
            bulk_g2s(sb + K3_OFF_RED, wr + nt * 160, 320, barFull + 120);
            for (int kt = 0; kt < K3_NPRE; kt++) bulk_g2s(sb + K3_OFF_B + kt * K3_BT, img + kt * K3_BT, K3_BT, barFull + 8 * kt);
        }
        __syncwarp();
        cluster_arrive();
        cluster_wait();
        if (lane == 0) {
            uint32_t rank; asm("mov.u32 %0, %%cluster_ctarank;" : "=r"(rank));
            pdl_wait();
            TL(2, 1);
            #pragma unroll 1
            for (int kt = 0; kt < 10; kt++) {
                if ((kt & 1) == (int)rank) tma_2d_mc(sb + kt * 8192, &tmO, kt * 64, mt * 64, barFull + 8 * kt, (uint16_t)3);
                if (kt == K3_NB - 1) mbar_wait(barFull + 128, 0);
                if (kt >= K3_NPRE && kt < K3_NB) bulk_g2s(sb + K3_OFF_B + kt * K3_BT, img + kt * K3_BT, K3_BT, barFull + 8 * kt);
            }
            #pragma unroll 1
            for (int j = 0; j < 10 - K3_NB; j++) {
                mbar_wait(barEmpty + 8 * j, 0);
                bulk_g2s(sb + K3_OFF_B + j * K3_BT, img + (K3_NB + j) * K3_BT, K3_BT, barFull + 8 * (K3_NB + j));
            }
            if (b == 0) g_epoch = g_epoch + 1;
            mbar_wait(barEmpty + 24, 0);
            TL(3, 0);
            if (b < 96) bulk_g2s(sb + K3_OFF_WG, g_wimg + b * 40960, 40960, barFull + 112);
            if (b >= 88) bulk_g2s(sb + K3_OFF_WD, g_wimg + WIMG_DOWN + (b - 88) * 49152, 49152, barFull + 112);
        }
        __syncwarp();
    } else {
        cluster_arrive();
        cluster_wait();
    }

    const int tt = tid - 128, tw = warp - 4;
    if (tt == 0) TL(3, 5);
    float* s_red = (float*)(smem + K3_OFF_RED);
    mbar_wait_warp(barFull + 112, 0);
    if (tt == 0) TL(3, 6);
    uint4 wA[10], wB[12];
    if (b < 96) {
        #pragma unroll
        for (int i = 0; i < 10; i++) wA[i] = lds_v4(sb + K3_OFF_WG + tw * 5120 + i * 512 + lane * 16);
    }
    if (b >= 88) {
        #pragma unroll
        for (int i = 0; i < 12; i++) wB[i] = lds_v4(sb + K3_OFF_WD + tw * 6144 + i * 512 + lane * 16);
    }
    pdl_wait();
    if (tw >= 8 - K3_KPOLL) {
        pause((7 - tw) * K3_KGAP);
        uint4 kv;
        uint32_t it = 0;
        bool ok;
        do {
            kv = ldx_v4(g_xc + XC_KEYS + nt * 512 + lane * 16);
            ok = __all_sync(~0u, valid4(kv));
            if (++it > (1u << 22)) __trap();
        } while (!ok && !lds_flag(barFull + 192));
        if (ok) {
            if (lane == 0) { TL(3, 1); TLC(4, 24); }
            uint32_t k0 = kv.x, k1 = kv.y;
            warp_top2(k0, k1);
            uint32_t* sel = (uint32_t*)(smem + K3_OFF_SEL);
            if (lane == 0) { sel[0] = k0; sel[1] = k1; }
            if (kv.x == k0) sel[2] = kv.z;
            if (kv.y == k0) sel[2] = kv.w;
            if (kv.x == k1) sel[3] = kv.z;
            if (kv.y == k1) sel[3] = kv.w;
            __syncwarp();
            if (lane == 0) sts_flag(barFull + 192);
        }
    }
    wait_flag(barFull + 192);
    if (tt == 0) { TL(3, 2); TLC(4, 25); }
    const uint4 sel = *(const uint4*)(smem + K3_OFF_SEL);
    {
        const int u = tt - 160, tk = tt < 160 ? tt >= 80 : (u >> 2) & 1;
        const uint32_t j = tk ? sel.y : sel.x;
        const uint32_t off = tt < 160 ? (tt - 80 * tk) * 16 : ((u >> 1) & 1) * 1280 + max(b - 88, 0) * 32 + (u & 1) * 16;
        const uint32_t dst = tt < 160 ? sb + K3_OFF_X + tk * K3_XS + off : sb + K3_OFF_HL + (u & 7) * 16;
        const uint8_t* src = g_xc + XC_CAND + ((key_row(j) >> 6) * 2 + (j & 1)) * 2560 + off;
        const bool on = tt < 160 ? b < 96 : (tt < 168 && b >= 88);
        if (on) {
            uint4 v;
            uint32_t it = 0;
            do {
                v = ldx_v4(src);
                if (++it > (1u << 22)) __trap();
            } while (!valid4(v));
            sts_v4(dst, v);
        }
    }
    named_bar<1, 256>();
    if (tt == 0) { TL(3, 3); TLC(4, 20); }
    if (b < 96) {
        gemv16<5>(wA, sb + K3_OFF_X + (tw & 3) * 320, K3_XS, s_red + tw, lane);
        if (tt == 0) TLC(4, 21);
        named_bar<1, 256>();
        if (tt == 0) TLC(4, 22);
        if (tt < 32) {
            const float4 pg = ((const float4*)s_red)[2 * tt], pu = ((const float4*)s_red)[2 * tt + 1];
            const float gb = round_bf((pg.x + pg.y) + (pg.z + pg.w));
            const float ub = round_bf((pu.x + pu.y) + (pu.z + pu.w));
            const float sl = round_bf(__fdividef(gb, 1.f + ex2(-1.4426950409f * gb)));
            const float v = sl * ub, vn = __shfl_down_sync(~0u, v, 1);
            if (!(tt & 1))
                asm volatile("st.relaxed.gpu.global.b32 [%0], %1;" :: "l"(g_xc + XC_HF + (tt >> 4) * (F_ * 2) + (b * 16 + (tt & 15)) * 2), "r"(pack_bf(v, vn)) : "memory");
            if (tt == 0) { TL(3, 4); TLC(4, 23); }
        }
    }
    if (b >= 88) {
        uint4 hv[2];
        poll(g_xc + XC_HF + tt * 16, tt < 128 ? 4096 : 0, hv);
        sts_v4(sb + K3_OFF_HF + (tt >= 192 ? K3_HS - F_ * 2 : 0) + tt * 16, hv[0]);
        if (tt < 128) sts_v4(sb + K3_OFF_HF + K3_HS - F_ * 2 + 4096 + tt * 16, hv[1]);
        const float rsel = round_bf(__uint_as_float((tt >> 4) & 1 ? sel.w : sel.z));
        const float sg = round_bf(__fdividef(1.f, 1.f + ex2(-1.4426950409f * rsel)));
        named_bar<1, 256>();
        if (tt == 0) { TL(4, 1); TLC(4, 16); }
        gemv16<6>(wB, sb + K3_OFF_HF + tw * 384, K3_HS, s_red + tw, lane);
        if (tt == 0) TLC(4, 17);
        named_bar<1, 256>();
        if (tt == 0) TLC(4, 18);
        if (tt < 32) {
            const int tk = tt >> 4;
            const float4 pa = ((const float4*)s_red)[2 * tt], pb = ((const float4*)s_red)[2 * tt + 1];
            const float y = ((pa.x + pa.y) + (pa.z + pa.w)) + ((pb.x + pb.y) + (pb.z + pb.w));
            const bf16* hl = (const bf16*)(smem + K3_OFF_HL) + tk * 32 + (tt & 15);
            const float ln = __bfloat162float(hl[0]), h = __bfloat162float(hl[16]);
            const float upd = round_bf(round_bf(y) * sg);
            out[(size_t)key_row(tk ? sel.y : sel.x) * D_ + (b - 88) * 16 + (tt & 15)] = __float2bfloat16_rn(h + round_bf(ln + upd));
            if (tt == 0) { TL(4, 2); TLC(4, 19); }
        }
    }
}

#define EXP_PROMO CU_TENSOR_MAP_L2_PROMOTION_L2_256B
typedef CUresult (*PFN_encodeTiled)(CUtensorMap*, CUtensorMapDataType, cuuint32_t, void*, const cuuint64_t*, const cuuint64_t*, const cuuint32_t*,
                                    const cuuint32_t*, CUtensorMapInterleave, CUtensorMapSwizzle, CUtensorMapL2promotion, CUtensorMapFloatOOBfill);

static void encode_map(PFN_encodeTiled fn, CUtensorMap* m, const void* base, int rank, const cuuint64_t* dims, const cuuint64_t* strides,
                       const cuuint32_t* box, CUtensorMapSwizzle sw, CUtensorMapL2promotion promo = EXP_PROMO) {
    cuuint32_t es[3] = {1, 1, 1};
    fn(m, CU_TENSOR_MAP_DATA_TYPE_BFLOAT16, rank, (void*)base, dims, strides, box, es, CU_TENSOR_MAP_INTERLEAVE_NONE, sw,
       promo, CU_TENSOR_MAP_FLOAT_OOB_FILL_NONE);
}

template <typename... KArgs, typename... Args>
static void launch(void (*kern)(KArgs...), int grid, int block, int smem, int cluster, bool pdl, Args... args) {
    cudaLaunchConfig_t cfg = {};
    cfg.gridDim = dim3(grid); cfg.blockDim = dim3(block); cfg.dynamicSmemBytes = smem; cfg.stream = cudaStreamPerThread;
    cudaLaunchAttribute at[2]; int n = 0;
    if (cluster > 1) { at[n].id = cudaLaunchAttributeClusterDimension; at[n].val.clusterDim.x = cluster; at[n].val.clusterDim.y = 1; at[n].val.clusterDim.z = 1; n++; }
    if (pdl) { at[n].id = cudaLaunchAttributeProgrammaticStreamSerialization; at[n].val.programmaticStreamSerializationAllowed = 1; n++; }
    cfg.attrs = at; cfg.numAttrs = n;
    cudaLaunchKernelEx(&cfg, kern, args...);
}

extern "C" void kernel_launch(void* const* d_in, const int* in_sizes, int n_in, void* d_out, int out_size) {
    const bf16* x = (const bf16*)d_in[0];
    const bf16* wqkv = (const bf16*)d_in[1];
    const bf16* wo = (const bf16*)d_in[2];
    const bf16* wr = (const bf16*)d_in[4];
    const bf16* wgate = (const bf16*)d_in[5];
    const bf16* wup = (const bf16*)d_in[6];
    const bf16* wdown = (const bf16*)d_in[7];
    bf16* out = (bf16*)d_out;

    static PFN_encodeTiled enc = nullptr;
    static void* o_ptr = nullptr;
    if (!enc) {
        cudaDriverEntryPointQueryResult qr;
        void* fn = nullptr;
        cudaGetDriverEntryPoint("cuTensorMapEncodeTiled", &fn, cudaEnableDefault, &qr);
        enc = (PFN_encodeTiled)fn;
        cudaGetSymbolAddress(&o_ptr, g_o);
        cudaFuncSetAttribute(k1_qkv, cudaFuncAttributeMaxDynamicSharedMemorySize, K1_SMEM);
        cudaFuncSetAttribute(k2_attn, cudaFuncAttributeMaxDynamicSharedMemorySize, K2_SMEM);
        cudaFuncSetAttribute(k3_tail, cudaFuncAttributeMaxDynamicSharedMemorySize, K3_SMEM);
    }
    CUtensorMap tmX, tmW, tmO, tmG, tmU, tmD, tmR;
    { cuuint64_t d[2] = {640, 2048}, s[1] = {1280}; cuuint32_t b[2] = {160, 64}; encode_map(enc, &tmR, x, 2, d, s, b, CU_TENSOR_MAP_SWIZZLE_NONE); }
    { cuuint64_t d[2] = {640, 2048}, s[1] = {1280}; cuuint32_t b[2] = {64, 128}; encode_map(enc, &tmX, x, 2, d, s, b, CU_TENSOR_MAP_SWIZZLE_128B); }
    { cuuint64_t d[2] = {1920, 640}, s[1] = {3840}; cuuint32_t b[2] = {64, 64}; encode_map(enc, &tmW, wqkv, 2, d, s, b, CU_TENSOR_MAP_SWIZZLE_128B); }
    { cuuint64_t d[2] = {640, 2048}, s[1] = {1280}; cuuint32_t b[2] = {64, 64}; encode_map(enc, &tmO, o_ptr, 2, d, s, b, CU_TENSOR_MAP_SWIZZLE_128B); }

    { cuuint64_t d[2] = {1536, 640}, s[1] = {3072}; cuuint32_t b[2] = {64, 160}; encode_map(enc, &tmG, wgate, 2, d, s, b, CU_TENSOR_MAP_SWIZZLE_128B);
      encode_map(enc, &tmU, wup, 2, d, s, b, CU_TENSOR_MAP_SWIZZLE_128B); }
    { cuuint64_t d[2] = {640, 1536}, s[1] = {1280}; cuuint32_t b[2] = {64, 192}; encode_map(enc, &tmD, wdown, 2, d, s, b, CU_TENSOR_MAP_SWIZZLE_128B); }

    launch(k1_qkv, 128, 384, K1_SMEM, 2, false, tmX, tmW, x, wqkv, wo);
    launch(k2_attn, 128 + K2_MOVERS, 512, K2_SMEM, 1, true, tmG, tmU, tmD, 0x007F007Fu, 0xFF80FF80u);
    launch(k3_tail, 128, 384, K3_SMEM, 2, true, tmO, tmR, wr, out);
}
```

```cpp
#include <cuda_runtime.h>
#include <cuda_bf16.h>
#include <cuda.h>
#include <stdint.h>

typedef __nv_bfloat16 bf16;

constexpr int S_ = 2048, D_ = 640, H_ = 32, F_ = 1536;
constexpr int HEAD_BYTES = 256 * 384;
constexpr uint32_t POLYMASK = 0xADADu;
constexpr float QSCALE = 0.22360679774997896f * 1.4426950408889634f;

__device__ __align__(1024) uint8_t g_qkv[3 * H_ * HEAD_BYTES];
__device__ __align__(128) float g_kmax[H_ * 128];
__device__ __align__(16) ulonglong2 g_rowstat[S_];
__device__ __align__(16) unsigned long long g_colsum[3 * D_];
__device__ unsigned g_epoch;
__device__ __align__(1024) bf16 g_o[S_ * D_];
#define K3_KW 2
constexpr int XC_PART = 0;
constexpr int XC_KEYS = XC_PART + S_ * 64;
constexpr int XC_CAND = XC_KEYS + 4 * 32 * 16 * K3_KW;
constexpr int XC_HF = XC_CAND + 32 * 2 * 2560;
constexpr int XC_BYTES = XC_HF + 2 * F_ * 2;
constexpr int XC_PER = XC_BYTES / (128 * 16);
static_assert(XC_BYTES == 128 * XC_PER * 16, "reset by 128 CTAs");
__device__ __align__(1024) uint8_t g_xc[XC_BYTES];
__device__ __align__(1024) uint8_t g_wimg[3 * D_ * F_ * 2];
__device__ __align__(1024) uint8_t g_wo_img[D_ * D_ * 2];

#define TL(k, slot) do {} while (0)
#define TLC(k, slot) do {} while (0)
__device__ __forceinline__ uint32_t smem_u32(const void* p) { return (uint32_t)__cvta_generic_to_shared(p); }
__device__ __forceinline__ uint64_t make_desc(uint32_t lo, uint32_t hi) {
    uint64_t d; asm("mov.b64 %0, {%1, %2};" : "=l"(d) : "r"(lo), "r"(hi));
    return d;
}
__device__ __forceinline__ void wg_fence() { asm volatile("wgmma.fence.sync.aligned;" ::: "memory"); }
__device__ __forceinline__ void wg_commit() { asm volatile("wgmma.commit_group.sync.aligned;" ::: "memory"); }
template<int N> __device__ __forceinline__ void wg_wait() { asm volatile("wgmma.wait_group.sync.aligned %0;" :: "n"(N) : "memory"); }
__device__ __forceinline__ void mbar_init(uint32_t bar, uint32_t cnt) { asm volatile("mbarrier.init.shared::cta.b64 [%0], %1;" :: "r"(bar), "r"(cnt)); }
__device__ __forceinline__ void mbar_expect_tx(uint32_t bar, uint32_t bytes) { asm volatile("mbarrier.arrive.expect_tx.shared::cta.b64 _, [%0], %1;" :: "r"(bar), "r"(bytes) : "memory"); }
__device__ __forceinline__ void mbar_arrive(uint32_t bar) { asm volatile("mbarrier.arrive.shared::cta.b64 _, [%0];" :: "r"(bar) : "memory"); }
__device__ __forceinline__ void mbar_arrive_cluster(uint32_t bar, uint32_t cta) {
    asm volatile("{\n.reg .b32 ra;\nmapa.shared::cluster.u32 ra, %0, %1;\n"
                 "mbarrier.arrive.shared::cluster.b64 _, [ra];\n}\n" :: "r"(bar), "r"(cta) : "memory");
}
__device__ __forceinline__ void mbar_wait(uint32_t bar, uint32_t parity) {
    asm volatile("{\n"
        ".reg .pred p;\n.reg .u32 c;\n"
        "mov.u32 c, 0;\n"
        "WAIT_LOOP:\n"
        "mbarrier.try_wait.parity.shared::cta.b64 p, [%0], %1;\n"
        "@p bra WAIT_DONE;\n"
        "add.u32 c, c, 1;\n"
        "setp.lt.u32 p, c, 0x1000000;\n"
        "@p bra WAIT_LOOP;\n"
        "trap;\n"
        "WAIT_DONE:\n"
        "}\n" :: "r"(bar), "r"(parity) : "memory");
}
__device__ __forceinline__ void mbar_wait_warp(uint32_t bar, uint32_t parity) {
    asm volatile("{\n"
        ".reg .pred p, q;\n.reg .u32 c;\n"
        "mov.u32 c, 0;\n"
        "WAIT_LOOP:\n"
        "mbarrier.try_wait.parity.shared::cta.b64 p, [%0], %1;\n"
        "vote.sync.all.pred p, p, 0xffffffff;\n"
        "@p bra.uni WAIT_DONE;\n"
        "add.u32 c, c, 1;\n"
        "setp.lt.u32 q, c, 0x1000000;\n"
        "@q bra.uni WAIT_LOOP;\n"
        "trap;\n"
        "WAIT_DONE:\n"
        "}\n" :: "r"(bar), "r"(parity) : "memory");
}
__device__ __forceinline__ void mbar_wait_cluster(uint32_t bar, uint32_t parity) {
    asm volatile("{\n"
        ".reg .pred p;\n.reg .u32 c;\n"
        "mov.u32 c, 0;\n"
        "WAIT_LOOP:\n"
        "mbarrier.try_wait.parity.acquire.cluster.shared::cta.b64 p, [%0], %1;\n"
        "@p bra WAIT_DONE;\n"
        "add.u32 c, c, 1;\n"
        "setp.lt.u32 p, c, 0x1000000;\n"
        "@p bra WAIT_LOOP;\n"
        "trap;\n"
        "WAIT_DONE:\n"
        "}\n" :: "r"(bar), "r"(parity) : "memory");
}
__device__ __forceinline__ void fence_mbar_init() { asm volatile("fence.mbarrier_init.release.cluster;" ::: "memory"); }
__device__ __forceinline__ void fence_async_smem() { asm volatile("fence.proxy.async.shared::cta;" ::: "memory"); }
__device__ __forceinline__ void bulk_g2s(uint32_t dst, const void* src, uint32_t bytes, uint32_t bar) {
    asm volatile("cp.async.bulk.shared::cluster.global.mbarrier::complete_tx::bytes [%0], [%1], %2, [%3];" :: "r"(dst), "l"(src), "r"(bytes), "r"(bar) : "memory");
}
__device__ __forceinline__ void bulk_g2s_mc(uint32_t dst, const void* src, uint32_t bytes, uint32_t bar, uint16_t mask) {
    asm volatile("cp.async.bulk.shared::cluster.global.mbarrier::complete_tx::bytes.multicast::cluster [%0], [%1], %2, [%3], %4;"
        :: "r"(dst), "l"(src), "r"(bytes), "r"(bar), "h"(mask) : "memory");
}
__device__ __forceinline__ void bulk_s2g(void* dst, uint32_t src, uint32_t bytes) {
    asm volatile("cp.async.bulk.global.shared::cta.bulk_group [%0], [%1], %2;" :: "l"(dst), "r"(src), "r"(bytes) : "memory");
}
__device__ __forceinline__ void bulk_commit() { asm volatile("cp.async.bulk.commit_group;" ::: "memory"); }
__device__ __forceinline__ void bulk_wait_all() { asm volatile("cp.async.bulk.wait_group 0;" ::: "memory"); }
__device__ __forceinline__ void prefetch_l2(const void* p, uint32_t bytes) {
    asm volatile("cp.async.bulk.prefetch.L2.global [%0], %1;" :: "l"(p), "r"(bytes) : "memory");
}
__device__ __forceinline__ void tma_2d(uint32_t dst, const CUtensorMap* tm, int c0, int c1, uint32_t bar) {
    asm volatile("cp.async.bulk.tensor.2d.shared::cluster.global.mbarrier::complete_tx::bytes [%0], [%1, {%3, %4}], [%2];"
        :: "r"(dst), "l"(tm), "r"(bar), "r"(c0), "r"(c1) : "memory");
}
__device__ __forceinline__ void tma_2d_mc(uint32_t dst, const CUtensorMap* tm, int c0, int c1, uint32_t bar, uint16_t mask) {
    asm volatile("cp.async.bulk.tensor.2d.shared::cluster.global.mbarrier::complete_tx::bytes.multicast::cluster [%0], [%1, {%3, %4}], [%2], %5;"
        :: "r"(dst), "l"(tm), "r"(bar), "r"(c0), "r"(c1), "h"(mask) : "memory");
}
__device__ __forceinline__ void tma_3d(uint32_t dst, const CUtensorMap* tm, int c0, int c1, int c2, uint32_t bar) {
    asm volatile("cp.async.bulk.tensor.3d.shared::cluster.global.mbarrier::complete_tx::bytes [%0], [%1, {%3, %4, %5}], [%2];"
        :: "r"(dst), "l"(tm), "r"(bar), "r"(c0), "r"(c1), "r"(c2) : "memory");
}
__device__ __forceinline__ void tmap_prefetch(const CUtensorMap* tm) { asm volatile("prefetch.tensormap [%0];" :: "l"(tm) : "memory"); }
__device__ __forceinline__ void cluster_arrive() { asm volatile("barrier.cluster.arrive.relaxed.aligned;" ::: "memory"); }
__device__ __forceinline__ void cluster_wait() { asm volatile("barrier.cluster.wait.acquire.aligned;" ::: "memory"); }
template<int ID, int N> __device__ __forceinline__ void named_bar() { asm volatile("bar.sync %0, %1;" :: "n"(ID), "n"(N) : "memory"); }
__device__ __forceinline__ void pdl_launch() { asm volatile("griddepcontrol.launch_dependents;" ::: "memory"); }
__device__ __forceinline__ void pdl_wait() { asm volatile("griddepcontrol.wait;" ::: "memory"); }
__device__ __forceinline__ uint4 ldg_v4(const void* p) {
    uint4 v; asm volatile("ld.relaxed.gpu.global.v4.b32 {%0,%1,%2,%3}, [%4];" : "=r"(v.x), "=r"(v.y), "=r"(v.z), "=r"(v.w) : "l"(p)); return v;
}
__device__ __forceinline__ uint32_t ldg_b32(const void* p) {
    uint32_t v; asm volatile("ld.relaxed.gpu.global.b32 %0, [%1];" : "=r"(v) : "l"(p)); return v;
}
__device__ __forceinline__ void st_tagged(void* p, float v, uint32_t tag) {
    asm volatile("st.relaxed.gpu.global.b64 [%0], %1;" :: "l"(p), "l"(((unsigned long long)tag << 32) | __float_as_uint(v)) : "memory");
}
__device__ __forceinline__ void st_tagged2(void* p, float v0, float v1, uint32_t tag) {
    asm volatile("st.relaxed.gpu.global.v2.b64 [%0], {%1, %2};" :: "l"(p), "l"(((unsigned long long)tag << 32) | __float_as_uint(v0)),
                 "l"(((unsigned long long)tag << 32) | __float_as_uint(v1)) : "memory");
}
__device__ __forceinline__ uint4 ld_tagged2(const void* p) {
    unsigned long long a, b;
    asm volatile("ld.relaxed.gpu.global.v2.b64 {%0, %1}, [%2];" : "=l"(a), "=l"(b) : "l"(p) : "memory");
    return make_uint4((uint32_t)a, (uint32_t)(a >> 32), (uint32_t)b, (uint32_t)(b >> 32));
}
__device__ __forceinline__ void stmatrix_x4(uint32_t addr, uint32_t r0, uint32_t r1, uint32_t r2, uint32_t r3) {
    asm volatile("stmatrix.sync.aligned.m8n8.x4.shared.b16 [%0], {%1, %2, %3, %4};" :: "r"(addr), "r"(r0), "r"(r1), "r"(r2), "r"(r3) : "memory");
}
__device__ __forceinline__ void named_bar_rr(int id, int n) { asm volatile("bar.sync %0, %1;" :: "r"(id), "r"(n) : "memory"); }
template<int ID, int N> __device__ __forceinline__ void named_arrive() { asm volatile("bar.arrive %0, %1;" :: "n"(ID), "n"(N) : "memory"); }
__device__ __forceinline__ void bulk_wait_read() { asm volatile("cp.async.bulk.wait_group.read 0;" ::: "memory"); }
__device__ __forceinline__ uint4 lds_v4(uint32_t a) {
    uint4 v; asm volatile("ld.shared.v4.b32 {%0,%1,%2,%3}, [%4];" : "=r"(v.x), "=r"(v.y), "=r"(v.z), "=r"(v.w) : "r"(a) : "memory"); return v;
}
__device__ __forceinline__ void sts_v4(uint32_t a, const uint4 v) {
    asm volatile("st.shared.v4.b32 [%0], {%1,%2,%3,%4};" :: "r"(a), "r"(v.x), "r"(v.y), "r"(v.z), "r"(v.w) : "memory");
}
__device__ __forceinline__ float bf_lo(uint32_t v) { return __uint_as_float(v << 16); }
__device__ __forceinline__ float bf_hi(uint32_t v) { return __uint_as_float(v & 0xffff0000u); }
__device__ __forceinline__ uint32_t pack_bf(float lo, float hi) {
    uint32_t r; asm("cvt.rn.bf16x2.f32 %0, %1, %2;" : "=r"(r) : "f"(hi), "f"(lo)); return r;
}
__device__ __forceinline__ float round_bf(float x) { return __uint_as_float(pack_bf(0.f, x)); }

__device__ __forceinline__ void mma_n240_ss(float (&d)[120], uint64_t da, uint64_t db, int scale_d) {
    asm volatile("{\n.reg .pred p;\nsetp.ne.b32 p, %122, 0;\n"
        "wgmma.mma_async.sync.aligned.m64n240k16.f32.bf16.bf16 "
        "{%0,%1,%2,%3,%4,%5,%6,%7,%8,%9,%10,%11,%12,%13,%14,%15,%16,%17,%18,%19,%20,%21,%22,%23,%24,%25,%26,%27,%28,%29,%30,%31,%32,%33,%34,%35,%36,%37,%38,%39,%40,%41,%42,%43,%44,%45,%46,%47,%48,%49,%50,%51,%52,%53,%54,%55,%56,%57,%58,%59,%60,%61,%62,%63,%64,%65,%66,%67,%68,%69,%70,%71,%72,%73,%74,%75,%76,%77,%78,%79,%80,%81,%82,%83,%84,%85,%86,%87,%88,%89,%90,%91,%92,%93,%94,%95,%96,%97,%98,%99,%100,%101,%102,%103,%104,%105,%106,%107,%108,%109,%110,%111,%112,%113,%114,%115,%116,%117,%118,%119}, %120, %121, p, 1, 1, 0, 1;\n}\n"
        : "+f"(d[0]), "+f"(d[1]), "+f"(d[2]), "+f"(d[3]), "+f"(d[4]), "+f"(d[5]), "+f"(d[6]), "+f"(d[7]), "+f"(d[8]), "+f"(d[9]), "+f"(d[10]), "+f"(d[11]), "+f"(d[12]), "+f"(d[13]), "+f"(d[14]), "+f"(d[15]), "+f"(d[16]), "+f"(d[17]), "+f"(d[18]), "+f"(d[19]), "+f"(d[20]), "+f"(d[21]), "+f"(d[22]), "+f"(d[23]), "+f"(d[24]), "+f"(d[25]), "+f"(d[26]), "+f"(d[27]), "+f"(d[28]), "+f"(d[29]), "+f"(d[30]), "+f"(d[31]), "+f"(d[32]), "+f"(d[33]), "+f"(d[34]), "+f"(d[35]), "+f"(d[36]), "+f"(d[37]), "+f"(d[38]), "+f"(d[39]), "+f"(d[40]), "+f"(d[41]), "+f"(d[42]), "+f"(d[43]), "+f"(d[44]), "+f"(d[45]), "+f"(d[46]), "+f"(d[47]), "+f"(d[48]), "+f"(d[49]), "+f"(d[50]), "+f"(d[51]), "+f"(d[52]), "+f"(d[53]), "+f"(d[54]), "+f"(d[55]), "+f"(d[56]), "+f"(d[57]), "+f"(d[58]), "+f"(d[59]), "+f"(d[60]), "+f"(d[61]), "+f"(d[62]), "+f"(d[63]), "+f"(d[64]), "+f"(d[65]), "+f"(d[66]), "+f"(d[67]), "+f"(d[68]), "+f"(d[69]), "+f"(d[70]), "+f"(d[71]), "+f"(d[72]), "+f"(d[73]), "+f"(d[74]), "+f"(d[75]), "+f"(d[76]), "+f"(d[77]), "+f"(d[78]), "+f"(d[79]), "+f"(d[80]), "+f"(d[81]), "+f"(d[82]), "+f"(d[83]), "+f"(d[84]), "+f"(d[85]), "+f"(d[86]), "+f"(d[87]), "+f"(d[88]), "+f"(d[89]), "+f"(d[90]), "+f"(d[91]), "+f"(d[92]), "+f"(d[93]), "+f"(d[94]), "+f"(d[95]), "+f"(d[96]), "+f"(d[97]), "+f"(d[98]), "+f"(d[99]), "+f"(d[100]), "+f"(d[101]), "+f"(d[102]), "+f"(d[103]), "+f"(d[104]), "+f"(d[105]), "+f"(d[106]), "+f"(d[107]), "+f"(d[108]), "+f"(d[109]), "+f"(d[110]), "+f"(d[111]), "+f"(d[112]), "+f"(d[113]), "+f"(d[114]), "+f"(d[115]), "+f"(d[116]), "+f"(d[117]), "+f"(d[118]), "+f"(d[119])
        : "l"(da), "l"(db), "r"(scale_d));
}

__device__ __forceinline__ void mma_n160_ss(float (&d)[80], uint64_t da, uint64_t db, int scale_d) {
    asm volatile("{\n.reg .pred p;\nsetp.ne.b32 p, %82, 0;\n"
        "wgmma.mma_async.sync.aligned.m64n160k16.f32.bf16.bf16 "
        "{%0,%1,%2,%3,%4,%5,%6,%7,%8,%9,%10,%11,%12,%13,%14,%15,%16,%17,%18,%19,%20,%21,%22,%23,%24,%25,%26,%27,%28,%29,%30,%31,%32,%33,%34,%35,%36,%37,%38,%39,%40,%41,%42,%43,%44,%45,%46,%47,%48,%49,%50,%51,%52,%53,%54,%55,%56,%57,%58,%59,%60,%61,%62,%63,%64,%65,%66,%67,%68,%69,%70,%71,%72,%73,%74,%75,%76,%77,%78,%79}, %80, %81, p, 1, 1, 1, 1;\n}\n"
        : "+f"(d[0]), "+f"(d[1]), "+f"(d[2]), "+f"(d[3]), "+f"(d[4]), "+f"(d[5]), "+f"(d[6]), "+f"(d[7]), "+f"(d[8]), "+f"(d[9]), "+f"(d[10]), "+f"(d[11]), "+f"(d[12]), "+f"(d[13]), "+f"(d[14]), "+f"(d[15]), "+f"(d[16]), "+f"(d[17]), "+f"(d[18]), "+f"(d[19]), "+f"(d[20]), "+f"(d[21]), "+f"(d[22]), "+f"(d[23]), "+f"(d[24]), "+f"(d[25]), "+f"(d[26]), "+f"(d[27]), "+f"(d[28]), "+f"(d[29]), "+f"(d[30]), "+f"(d[31]), "+f"(d[32]), "+f"(d[33]), "+f"(d[34]), "+f"(d[35]), "+f"(d[36]), "+f"(d[37]), "+f"(d[38]), "+f"(d[39]), "+f"(d[40]), "+f"(d[41]), "+f"(d[42]), "+f"(d[43]), "+f"(d[44]), "+f"(d[45]), "+f"(d[46]), "+f"(d[47]), "+f"(d[48]), "+f"(d[49]), "+f"(d[50]), "+f"(d[51]), "+f"(d[52]), "+f"(d[53]), "+f"(d[54]), "+f"(d[55]), "+f"(d[56]), "+f"(d[57]), "+f"(d[58]), "+f"(d[59]), "+f"(d[60]), "+f"(d[61]), "+f"(d[62]), "+f"(d[63]), "+f"(d[64]), "+f"(d[65]), "+f"(d[66]), "+f"(d[67]), "+f"(d[68]), "+f"(d[69]), "+f"(d[70]), "+f"(d[71]), "+f"(d[72]), "+f"(d[73]), "+f"(d[74]), "+f"(d[75]), "+f"(d[76]), "+f"(d[77]), "+f"(d[78]), "+f"(d[79])
        : "l"(da), "l"(db), "r"(scale_d));
}

#define D8(d,o) "+f"(d[o+0]), "+f"(d[o+1]), "+f"(d[o+2]), "+f"(d[o+3]), "+f"(d[o+4]), "+f"(d[o+5]), "+f"(d[o+6]), "+f"(d[o+7])
template<int SCALE_D>
__device__ __forceinline__ void mma_n64_rs(float (&d)[32], uint32_t a0, uint32_t a1, uint32_t a2, uint32_t a3, uint64_t db) {
    asm volatile("{\n"
        "wgmma.mma_async.sync.aligned.m64n64k16.f32.bf16.bf16 "
        "{%0,%1,%2,%3,%4,%5,%6,%7,%8,%9,%10,%11,%12,%13,%14,%15,"
        "%16,%17,%18,%19,%20,%21,%22,%23,%24,%25,%26,%27,%28,%29,%30,%31}, {%32,%33,%34,%35}, %36, %37, 1, 1, 0;\n}\n"
        : D8(d,0), D8(d,8), D8(d,16), D8(d,24)
        : "r"(a0), "r"(a1), "r"(a2), "r"(a3), "l"(db), "n"(SCALE_D));
}
template<int SCALE_D>
__device__ __forceinline__ void mma_n24_rs(float (&d)[12], uint32_t a0, uint32_t a1, uint32_t a2, uint32_t a3, uint64_t db) {
    asm volatile("{\n"
        "wgmma.mma_async.sync.aligned.m64n24k16.f32.bf16.bf16 "
        "{%0,%1,%2,%3,%4,%5,%6,%7,%8,%9,%10,%11}, {%12,%13,%14,%15}, %16, %17, 1, 1, 1;\n}\n"
        : "+f"(d[0]), "+f"(d[1]), "+f"(d[2]), "+f"(d[3]), "+f"(d[4]), "+f"(d[5]), "+f"(d[6]), "+f"(d[7]),
          "+f"(d[8]), "+f"(d[9]), "+f"(d[10]), "+f"(d[11])
        : "r"(a0), "r"(a1), "r"(a2), "r"(a3), "l"(db), "n"(SCALE_D));
}

constexpr int K1_STAGE = 49152, K1_NST = 4;
constexpr int K1_OFF_CS = K1_NST * K1_STAGE;
constexpr int K1_OFF_RS = K1_OFF_CS + 1024;
constexpr int K1_OFF_PART = K1_OFF_RS + 1024;
constexpr int K1_OFF_BAR = K1_OFF_PART + 256;
constexpr int K1_OFF_KM = K1_OFF_BAR + 128;
constexpr int K1_SMEM = K1_OFF_KM + 384;
constexpr uint32_t KAUX0 = 0x43C03F80u, KAUX1 = 0x3B2CBFCDu;

__global__ void __launch_bounds__(384, 1)
k1_qkv(const __grid_constant__ CUtensorMap tmX, const __grid_constant__ CUtensorMap tmW, const bf16* __restrict__ x, const bf16* __restrict__ W,
       const bf16* __restrict__ wo) {
    extern __shared__ __align__(1024) uint8_t smem[];
    const uint32_t sb = smem_u32(smem);
    const uint32_t barFull = sb + K1_OFF_BAR, barEmpty = barFull + 32, barStat = barFull + 64;
    const int tid = threadIdx.x, warp = tid >> 5, lane = tid & 31;
    uint32_t rank; asm("mov.u32 %0, %%cluster_ctarank;" : "=r"(rank));
    const int pair = blockIdx.x >> 1, nt = pair & 7, mt = (pair >> 3) * 2 + (int)rank;
    pdl_launch();
    if (tid == 0) TL(0, 0);

    if (warp == 8) {
        if (lane == 0) {
            tmap_prefetch(&tmX);
            tmap_prefetch(&tmW);
            for (int s = 0; s < K1_NST; s++) { mbar_init(barFull + 8 * s, 1); mbar_init(barEmpty + 8 * s, 4); }
            mbar_init(barStat, 3);
            fence_mbar_init();
            fence_async_smem();
            mbar_expect_tx(barFull, K1_STAGE);
            tma_2d(sb, &tmX, 0, mt * 128, barFull);
            for (int s = 1; s < K1_NST; s++) mbar_expect_tx(barFull + 8 * s, K1_STAGE);
        }
        __syncwarp();
        if (lane == 0) TL(0, 6);
        cluster_arrive();
        cluster_wait();
        if (lane == 0) TL(0, 7);
        if (lane == 0) {
            const int a = 2 * (int)rank;
            for (int kt = 0; kt < 10; kt++) {
                const int s = kt & 3;
                const uint32_t st = sb + s * K1_STAGE, bar = barFull + 8 * s;
                if (kt >= K1_NST) {
                    mbar_wait(barEmpty + 8 * s, ((kt >> 2) - 1) & 1);
                    mbar_expect_tx(bar, K1_STAGE);
                }
                tma_2d_mc(st + 16384 + a * 8192, &tmW, nt * 240 + a * 64, kt * 64, bar, (uint16_t)3);
                tma_2d_mc(st + 16384 + (a + 1) * 8192, &tmW, nt * 240 + (a + 1) * 64, kt * 64, bar, (uint16_t)3);
                if (kt > 0) tma_2d(st, &tmX, kt * 64, mt * 128, bar);
                TL(0, 20 + kt);
            }
        }
        __syncwarp();
    } else if (warp > 8) {
        cluster_arrive();
        const int hw = warp - 9, b = blockIdx.x;
        uint4 wv[14], xv[15];
        #pragma unroll
        for (int i = 0; i < 3; i++) {
            const int p = hw + 3 * i;
            #pragma unroll
            for (int c = 0; c < 5; c++) {
                xv[i * 5 + c] = make_uint4(0, 0, 0, 0);
                if (p < 8) xv[i * 5 + c] = ldg_v4((const uint4*)(x + (size_t)(b * 16 + 2 * p + (lane >> 4)) * D_) + (lane & 15) + 16 * c);
            }
        }
        #pragma unroll
        for (int i = 0; i < 14; i++) {
            const int it = hw + 3 * i;
            wv[i] = make_uint4(0, 0, 0, 0);
            if (b < 120 && it < 40) wv[i] = ldg_v4((const uint4*)(W + (size_t)(it * 16 + (lane >> 1)) * 1920 + b * 16 + (lane & 1) * 8));
        }
        const uint32_t tag = ldg_b32(&g_epoch) + 1;
        #pragma unroll
        for (int i = 0; i < 3; i++) {
            const int p = hw + 3 * i;
            float s = 0.f;
            #pragma unroll
            for (int c = 0; c < 5; c++) {
                const uint4 v = xv[i * 5 + c];
                s += (bf_lo(v.x) + bf_hi(v.x)) + (bf_lo(v.y) + bf_hi(v.y)) + (bf_lo(v.z) + bf_hi(v.z)) + (bf_lo(v.w) + bf_hi(v.w));
            }
            #pragma unroll
            for (int o = 1; o < 16; o <<= 1) s += __shfl_xor_sync(~0u, s, o);
            const float mu = s * (1.f / D_);
            float q = 0.f;
            #pragma unroll
            for (int c = 0; c < 5; c++) {
                const uint4 v = xv[i * 5 + c];
                float d;
                d = bf_lo(v.x) - mu; q += d * d; d = bf_hi(v.x) - mu; q += d * d;
                d = bf_lo(v.y) - mu; q += d * d; d = bf_hi(v.y) - mu; q += d * d;
                d = bf_lo(v.z) - mu; q += d * d; d = bf_hi(v.z) - mu; q += d * d;
                d = bf_lo(v.w) - mu; q += d * d; d = bf_hi(v.w) - mu; q += d * d;
            }
            #pragma unroll
            for (int o = 1; o < 16; o <<= 1) q += __shfl_xor_sync(~0u, q, o);
            if (p < 8 && (lane & 15) == 0) st_tagged2(&g_rowstat[b * 16 + 2 * p + (lane >> 4)], mu, rsqrtf(q * (1.f / D_) + 1e-5f), tag);
        }
        if (tid == 288) { TL(0, 8); prefetch_l2((const uint8_t*)wo + b * 6400, 6400); }
        float cs[8];
        #pragma unroll
        for (int j = 0; j < 8; j++) cs[j] = 0.f;
        #pragma unroll
        for (int i = 0; i < 14; i++) {
            cs[0] += bf_lo(wv[i].x); cs[1] += bf_hi(wv[i].x); cs[2] += bf_lo(wv[i].y); cs[3] += bf_hi(wv[i].y);
            cs[4] += bf_lo(wv[i].z); cs[5] += bf_hi(wv[i].z); cs[6] += bf_lo(wv[i].w); cs[7] += bf_hi(wv[i].w);
        }
        #pragma unroll
        for (int j = 0; j < 8; j++) {
            #pragma unroll
            for (int o = 2; o < 32; o <<= 1) cs[j] += __shfl_xor_sync(~0u, cs[j], o);
        }
        float* part = (float*)(smem + K1_OFF_PART);
        if (lane < 2) {
            #pragma unroll
            for (int j = 0; j < 8; j++) part[hw * 16 + lane * 8 + j] = cs[j];
        }
        named_bar<2, 96>();
        const int ht = tid - 288;
        if (ht < 16 && b < 120) st_tagged(&g_colsum[b * 16 + ht], part[ht] + part[16 + ht] + part[32 + ht], tag);
        if (tid == 288) TL(0, 9);
        float* scs = (float*)(smem + K1_OFF_CS);
        float2* srs = (float2*)(smem + K1_OFF_RS);
        {
            const bool hr = ht < 32, hc = ht < 24;
            uint4 r0, r1, c0, c1;
            int it = 0;
            bool ok;
            do {
                r0 = ld_tagged2(&g_rowstat[mt * 128 + ht]);
                c0 = ld_tagged2(&g_colsum[nt * 240 + 2 * ht]);
                r1 = hr ? ld_tagged2(&g_rowstat[mt * 128 + 96 + ht]) : r0;
                c1 = hc ? ld_tagged2(&g_colsum[nt * 240 + 192 + 2 * ht]) : c0;
                ok = r0.y == tag && r0.w == tag && c0.y == tag && c0.w == tag && r1.y == tag && r1.w == tag && c1.y == tag && c1.w == tag;
                if (++it > (1 << 22)) __trap();
            } while (!ok);
            srs[ht] = make_float2(__uint_as_float(r0.x), __uint_as_float(r0.z));
            *(float2*)(scs + 2 * ht) = make_float2(__uint_as_float(c0.x), __uint_as_float(c0.z));
            if (hr) srs[96 + ht] = make_float2(__uint_as_float(r1.x), __uint_as_float(r1.z));
            if (hc) *(float2*)(scs + 192 + 2 * ht) = make_float2(__uint_as_float(c1.x), __uint_as_float(c1.z));
        }
        __syncwarp();
        if (lane == 0) mbar_arrive(barStat);
        if (ht == 0) TL(0, 5);
        uint4 wt[2][4];
        #pragma unroll
        for (int i = 0; i < 2; i++) {
            const int item = b * 100 + ht + 96 * i, k = ((item >> 3) / 20) * 8 + (item & 7), grp = (item >> 3) % 20;
            if (i == 0 || ht < 4) {
                #pragma unroll
                for (int c = 0; c < 4; c++) wt[i][c] = ldg_v4(wo + (size_t)k * D_ + grp * 32 + c * 8);
            }
        }
        #pragma unroll
        for (int i = 0; i < 2; i++) {
            const int item = b * 100 + ht + 96 * i, k = ((item >> 3) / 20) * 8 + (item & 7), grp = (item >> 3) % 20;
            if (i == 0 || ht < 4) {
                uint8_t* dst = g_wo_img + ((grp / 5) * 10 + (k >> 6)) * 20480 + ((k >> 3) & 7) * 2560 + (grp % 5) * 512 + (k & 7) * 16;
                *(uint4*)(dst) = make_uint4(wt[i][0].x, wt[i][1].x, wt[i][2].x, wt[i][3].x);
                *(uint4*)(dst + 128) = make_uint4(wt[i][0].y, wt[i][1].y, wt[i][2].y, wt[i][3].y);
                *(uint4*)(dst + 256) = make_uint4(wt[i][0].z, wt[i][1].z, wt[i][2].z, wt[i][3].z);
                *(uint4*)(dst + 384) = make_uint4(wt[i][0].w, wt[i][1].w, wt[i][2].w, wt[i][3].w);
            }
        }
        cluster_wait();
    } else {
        cluster_arrive();
        cluster_wait();
        const int wg = warp >> 2, w4 = warp & 3, g = lane >> 2, t = lane & 3;
        float acc[120];
        const uint32_t hiA = 64u | (1u << 30), hiB = 64u | (1u << 30);
        #pragma unroll 1
        for (int kt = 0; kt < 10; kt++) {
            const int s = kt & 3;
            const uint32_t st = sb + s * K1_STAGE;
            mbar_wait(barFull + 8 * s, (kt >> 2) & 1);
            if (tid == 0 && kt == 0) TL(0, 1);
            if (tid == 0) TL(0, 10 + kt);
            const uint32_t sa = (st & 0x3FFFF) >> 4;
            const uint32_t loA = sa + wg * 512 + (1u << 16), loB = sa + 1024 + (512u << 16);
            wg_fence();
            #pragma unroll
            for (int kk = 0; kk < 4; kk++)
                mma_n240_ss(acc, make_desc(loA + 2 * kk, hiA), make_desc(loB + 128 * kk, hiB), (kt | kk) != 0);
            wg_commit();
            if (kt > 0) {
                wg_wait<1>();
                if (kt <= 6 && (tid & 127) == 0) {
                    const uint32_t eb = barEmpty + 8 * ((kt - 1) & 3);
                    mbar_arrive_cluster(eb, 0);
                    mbar_arrive_cluster(eb, 1);
                }
            }
        }
        wg_wait<0>();
        #pragma unroll
        for (int i = 0; i < 120; i++) asm volatile("" : "+f"(acc[i]) :: "memory");
        if (tid == 0) TL(0, 2);
        mbar_wait(barStat, 0);
        if (tid == 0) TL(0, 3);

        const float* scs = (const float*)(smem + K1_OFF_CS);
        const float2* srs = (const float2*)(smem + K1_OFF_RS);
        const int r0 = wg * 64 + w4 * 16 + g;
        const float2 st0 = srs[r0], st1 = srs[r0 + 8];
        const int grp0 = wg * 8 + w4 * 2;
        const bool poly0 = (POLYMASK >> grp0) & 1, poly1 = (POLYMASK >> (grp0 + 1)) & 1;
        const uint32_t kx0 = (t & 1) ? (poly0 ? KAUX1 : 0u) : (poly0 ? KAUX0 : 0x3F80u), kx1 = (t & 1) ? (poly1 ? KAUX1 : 0u) : (poly1 ? KAUX0 : 0x3F80u);
        const uint32_t vx0 = (t & 1) ? 0u : (poly0 ? 0xBF80u : 0x3F80u), vx1 = (t & 1) ? 0u : (poly1 ? 0xBF80u : 0x3F80u);
        uint32_t* skm = (uint32_t*)(smem + K1_OFF_KM);
        uint8_t* gdir = g_qkv + (size_t)(nt * 12) * HEAD_BYTES + mt * 6144 + grp0 * 384 + g * 16 + 4 * t;
        #define K1_PAIR(P) do { \
            const int G = nt * 12 + 2 * P, type = G >> 5; \
            float ra = st0.y, rb = st1.y; \
            uint32_t x0 = 0, x1 = 0; \
            if (type == 0) { ra *= QSCALE; rb *= QSCALE; } \
            if (type == 1) { x0 = kx0; x1 = kx1; } \
            if (type == 2) { if (poly0) ra = -ra; if (poly1) rb = -rb; x0 = vx0; x1 = vx1; } \
            const float ma = -st0.x * ra, mb = -st1.x * rb; \
            float v[5][4]; \
            uint32_t r[5][2]; \
            _Pragma("unroll") \
            for (int jm = 0; jm < 5; jm++) { \
                const int j = P * 5 + jm; \
                const float2 c = *(const float2*)(scs + 8 * j + 2 * t); \
                v[jm][0] = fmaf(acc[4 * j], ra, c.x * ma); v[jm][1] = fmaf(acc[4 * j + 1], ra, c.y * ma); \
                v[jm][2] = fmaf(acc[4 * j + 2], rb, c.x * mb); v[jm][3] = fmaf(acc[4 * j + 3], rb, c.y * mb); \
                r[jm][0] = pack_bf(v[jm][0], v[jm][1]); r[jm][1] = pack_bf(v[jm][2], v[jm][3]); \
            } \
            const uint32_t e0 = t < 2 ? r[2][0] : x0, e1 = t < 2 ? r[2][1] : x1, e2 = t < 2 ? x0 : r[2][0], e3 = t < 2 ? x1 : r[2][1]; \
            uint8_t* d = gdir + (size_t)(2 * P) * HEAD_BYTES;        \
            *(uint32_t*)(d) = r[0][0]; *(uint32_t*)(d + 128) = r[1][0]; *(uint32_t*)(d + 256) = e0; \
            *(uint32_t*)(d + 384) = r[0][1]; *(uint32_t*)(d + 512) = r[1][1]; *(uint32_t*)(d + 640) = e1; \
            d += HEAD_BYTES; \
            *(uint32_t*)(d) = r[3][0]; *(uint32_t*)(d + 128) = r[4][0]; *(uint32_t*)(d + 256) = e2; \
            *(uint32_t*)(d + 384) = r[3][1]; *(uint32_t*)(d + 512) = r[4][1]; *(uint32_t*)(d + 640) = e3; \
            if (type == 1) { \
                float nA0, nA1, nB0, nB1; \
                nA0 = fmaf(v[0][0], v[0][0], fmaf(v[0][1], v[0][1], fmaf(v[1][0], v[1][0], v[1][1] * v[1][1]))); \
                nA1 = fmaf(v[0][2], v[0][2], fmaf(v[0][3], v[0][3], fmaf(v[1][2], v[1][2], v[1][3] * v[1][3]))); \
                nB0 = fmaf(v[3][0], v[3][0], fmaf(v[3][1], v[3][1], fmaf(v[4][0], v[4][0], v[4][1] * v[4][1]))); \
                nB1 = fmaf(v[3][2], v[3][2], fmaf(v[3][3], v[3][3], fmaf(v[4][2], v[4][2], v[4][3] * v[4][3]))); \
                const float q0 = fmaf(v[2][0], v[2][0], v[2][1] * v[2][1]), q1 = fmaf(v[2][2], v[2][2], v[2][3] * v[2][3]); \
                if (t < 2) { nA0 += q0; nA1 += q1; } else { nB0 += q0; nB1 += q1; } \
                nA0 += __shfl_xor_sync(~0u, nA0, 1); nA1 += __shfl_xor_sync(~0u, nA1, 1); \
                nB0 += __shfl_xor_sync(~0u, nB0, 1); nB1 += __shfl_xor_sync(~0u, nB1, 1); \
                nA0 += __shfl_xor_sync(~0u, nA0, 2); nA1 += __shfl_xor_sync(~0u, nA1, 2); \
                nB0 += __shfl_xor_sync(~0u, nB0, 2); nB1 += __shfl_xor_sync(~0u, nB1, 2); \
                  \
                const uint32_t mA = __reduce_max_sync(~0u, max(__float_as_uint(nA0), __float_as_uint(nA1))); \
                const uint32_t mB = __reduce_max_sync(~0u, max(__float_as_uint(nB0), __float_as_uint(nB1))); \
                if (lane == 0) { skm[2 * P * 8 + warp] = mA; skm[(2 * P + 1) * 8 + warp] = mB; } \
            } \
        } while (0)
        K1_PAIR(0); K1_PAIR(1); K1_PAIR(2); K1_PAIR(3); K1_PAIR(4); K1_PAIR(5);
        #undef K1_PAIR
        if (nt * 12 + 11 >= 32 && nt * 12 < 64) {
            named_bar<1, 256>();
            const int G = nt * 12 + (tid >> 3);
            if (tid < 96 && (G >> 5) == 1) g_kmax[(G & 31) * 128 + mt * 8 + (tid & 7)] = __uint_as_float(skm[tid]);
        }
        if (tid == 0) TL(0, 4);
    }
}

#define K2_UNR 2
#define K2_FIRST 2
constexpr int K2_OFF_BAR = 2 * HEAD_BYTES;
constexpr int K2_OFF_STG = K2_OFF_BAR + 256;
constexpr int K2_SMEM = K2_OFF_STG + 24576;

__device__ __forceinline__ float ex2(float y) { float e; asm("ex2.approx.ftz.f32 %0, %1;" : "=f"(e) : "f"(y)); return e; }
__device__ __forceinline__ uint32_t exp_pair_mufu(float y0, float y1) { return pack_bf(ex2(y0), ex2(y1)); }
__device__ __forceinline__ uint32_t hfma2(uint32_t a, uint32_t b, uint32_t c) {
    uint32_t r; asm("fma.rn.bf16x2 %0, %1, %2, %3;" : "=r"(r) : "r"(a), "r"(b), "r"(c)); return r;
}
__device__ __forceinline__ uint32_t exp_pair_poly(float y0, float y1, uint32_t cm, uint32_t ce) {
    const uint32_t G = __byte_perm(__float_as_uint(y0), __float_as_uint(y1), 0x6521);
    uint32_t w, z;
    asm("lop3.b32 %0, %1, %2, 0x3F003F00, 0xEA;" : "=r"(w) : "r"(G), "r"(cm));
    asm("lop3.b32 %0, %1, %2, 0x00030003, 0xEA;" : "=r"(z) : "r"(G), "r"(ce));
    return hfma2(G, w, z);
}
template<int MASK8>
__device__ __forceinline__ void softmax8(float (&s)[32], uint32_t (&p)[16], uint32_t cm, uint32_t ce) {
    #pragma unroll
    for (int i = 0; i < 32; i++) asm volatile("" : "+f"(s[i]) :: "memory");
    #pragma unroll
    for (int gi = 0; gi < 8; gi++) {
        if ((MASK8 >> gi) & 1) {
            p[2 * gi] = exp_pair_poly(s[4 * gi], s[4 * gi + 1], cm, ce);
            p[2 * gi + 1] = exp_pair_poly(s[4 * gi + 2], s[4 * gi + 3], cm, ce);
        } else {
            p[2 * gi] = exp_pair_mufu(s[4 * gi], s[4 * gi + 1]);
            p[2 * gi + 1] = exp_pair_mufu(s[4 * gi + 2], s[4 * gi + 3]);
        }
    }
}
__device__ __forceinline__ uint32_t movm(uint32_t a) {
    uint32_t d; asm volatile("movmatrix.sync.aligned.m8n8.trans.b16 %0, %1;" : "=r"(d) : "r"(a)); return d;
}
__device__ __forceinline__ void attn_store(float (&o)[12], int row0, int head, int lane) {
    const int odd = head & 1;
    const int src = (lane & ~3) | (odd ? 0 : 2);
    const float l0 = __shfl_sync(~0u, o[8], src), l1 = __shfl_sync(~0u, o[10], src);
    const float r0 = __fdividef(1.f, l0), r1 = __fdividef(1.f, l1);
    uint8_t* p = (uint8_t*)g_o + (row0 >> 6) * 81920 + (head >> 1) * 5120 + ((row0 >> 3) & 7) * 128 + lane * 4;
    uint8_t* p0 = p + (odd ? 3072 : 0);
    const uint32_t m0 = movm(pack_bf(o[0] * r0, o[1] * r0)), m1 = movm(pack_bf(o[2] * r1, o[3] * r1));
    const uint32_t m2 = movm(pack_bf(o[4] * r0, o[5] * r0)), m3 = movm(pack_bf(o[6] * r1, o[7] * r1));
    const uint32_t m4 = movm(pack_bf(o[8] * r0, o[9] * r0)), m5 = movm(pack_bf(o[10] * r1, o[11] * r1));
    *(uint32_t*)(p0) = m0;
    *(uint32_t*)(p0 + 128) = m1;
    *(uint32_t*)(p0 + 1024) = m2;
    *(uint32_t*)(p0 + 1024 + 128) = m3;
    if ((lane < 16) != (bool)odd) {
        *(uint32_t*)(p + 2048) = m4;
        *(uint32_t*)(p + 2048 + 128) = m5;
    }
}

__device__ __forceinline__ void load_q(uint32_t sQ, int mt, uint32_t (&q)[8]) {
    const int lane = threadIdx.x & 31;
    const uint32_t base = sQ + ((threadIdx.x >> 7) * 16 + mt * 8 + ((threadIdx.x >> 5) & 3) * 2 + ((lane >> 3) & 1)) * 384 + (lane & 7) * 16;
    asm volatile("ldmatrix.sync.aligned.m8n8.x4.shared.b16 {%0,%1,%2,%3}, [%4];" : "=r"(q[0]), "=r"(q[1]), "=r"(q[2]), "=r"(q[3]) : "r"(base + (lane >> 4) * 128) : "memory");
    asm volatile("ldmatrix.sync.aligned.m8n8.x4.shared.b16 {%0,%1,%2,%3}, [%4];" : "=r"(q[4]), "=r"(q[5]), "=r"(q[6]), "=r"(q[7])
                 : "r"(lane < 16 ? base + 256 : sQ - K2_OFF_STG + K2_OFF_BAR + 128) : "memory");
}
__device__ __forceinline__ uint32_t patch_q(uint32_t (&q)[8], float km2, bool isaux, int t) {
    uint32_t unsafe = 0;
    #pragma unroll
    for (int r = 0; r < 2; r++) {
        float n2 = 0;
        #pragma unroll
        for (int i = 0; i < 3; i++) {
            const float lo = bf_lo(q[2 * i + r]), hi = bf_hi(q[2 * i + r]);
            n2 = fmaf(lo, lo, fmaf(hi, hi, n2));
        }
        n2 += __shfl_xor_sync(~0u, n2, 1);
        n2 += __shfl_xor_sync(~0u, n2, 2);
        float rt; asm("sqrt.approx.f32 %0, %1;" : "=f"(rt) : "f"(n2 * km2));
        const float B = rt * 1.01f + 0.01f;
        unsafe |= !(B <= 47.25f);
        const uint32_t nb = ((__float_as_uint(B) + 0xffffu) >> 16) | 0x8000u;
        if (isaux) q[4 + r] = (t & 1) ? 0x3F803F80u : (nb | 0x3F800000u);
    }
    return unsafe;
}
__device__ __forceinline__ uint32_t wg_any(uint32_t v, int wg) {
    asm volatile("{\n.reg .pred p, q;\nsetp.ne.u32 q, %0, 0;\nbar.red.or.pred p, %1, 128, q;\nselp.u32 %0, 1, 0, p;\n}\n" : "+r"(v) : "r"(1 + wg) : "memory");
    return v;
}
__device__ __forceinline__ void attn_safe(uint32_t sK, uint32_t sV, uint32_t sBar, const uint32_t (&q0)[8], int rowbase, int head) {
    const int tid = threadIdx.x, lane = tid & 31, t = lane & 3;
    const bool isaux = (t < 2) == (bool)(head & 1);
    for (int j = 0; j < 9; j++) mbar_wait(sBar + j * 8, 0);
    uint32_t q1[8];
    load_q(sK + K2_OFF_STG, 1, q1);
    #pragma unroll 1
    for (int mt = 0; mt < 2; mt++) {
        uint4 qa = mt ? make_uint4(q1[0], q1[1], q1[2], q1[3]) : make_uint4(q0[0], q0[1], q0[2], q0[3]);
        uint4 qb = mt ? make_uint4(q1[4], q1[5], 0, 0) : make_uint4(q0[4], q0[5], 0, 0);
        if (isaux) { qb.x = 0; qb.y = 0; }
        float o[12], s[32];
        uint32_t p[16];
        #pragma unroll
        for (int i = 0; i < 12; i++) { o[i] = 0.f; asm volatile("" : "+f"(o[i]) :: "memory"); }
        float m0 = -INFINITY, m1 = -INFINITY;
        #pragma unroll 1
        for (int u = 0; u < 32; u++) {
            const uint32_t kb = (((sK + u * 3072) & 0x3FFFF) >> 4) + (8u << 16), vb = (((sV + u * 3072) & 0x3FFFF) >> 4) + (24u << 16);
            wg_fence();
            mma_n64_rs<0>(s, qa.x, qa.y, qa.z, qa.w, make_desc(kb, 24));
            mma_n64_rs<1>(s, qb.x, qb.y, qb.z, qb.w, make_desc(kb + 16, 24));
            wg_commit();
            wg_wait<0>();
            #pragma unroll
            for (int i = 0; i < 32; i++) asm volatile("" : "+f"(s[i]) :: "memory");
            float n0 = m0, n1 = m1;
            #pragma unroll
            for (int gi = 0; gi < 8; gi++) {
                n0 = fmaxf(n0, fmaxf(s[4 * gi], s[4 * gi + 1]));
                n1 = fmaxf(n1, fmaxf(s[4 * gi + 2], s[4 * gi + 3]));
            }
            n0 = fmaxf(n0, __shfl_xor_sync(~0u, n0, 1)); n0 = fmaxf(n0, __shfl_xor_sync(~0u, n0, 2));
            n1 = fmaxf(n1, __shfl_xor_sync(~0u, n1, 1)); n1 = fmaxf(n1, __shfl_xor_sync(~0u, n1, 2));
            const float a0 = ex2(m0 - n0), a1 = ex2(m1 - n1);
            m0 = n0; m1 = n1;
            #pragma unroll
            for (int c = 0; c < 3; c++) { o[4 * c] *= a0; o[4 * c + 1] *= a0; o[4 * c + 2] *= a1; o[4 * c + 3] *= a1; }
            const uint32_t mask8 = (POLYMASK >> ((u & 1) * 8)) & 0xFF;
            #pragma unroll
            for (int gi = 0; gi < 8; gi++) {
                const uint32_t sg = ((mask8 >> gi) & 1) ? 0x80008000u : 0u;
                p[2 * gi] = pack_bf(ex2(s[4 * gi] - m0), ex2(s[4 * gi + 1] - m0)) ^ sg;
                p[2 * gi + 1] = pack_bf(ex2(s[4 * gi + 2] - m1), ex2(s[4 * gi + 3] - m1)) ^ sg;
            }
            #pragma unroll
            for (int i = 0; i < 12; i++) asm volatile("" : "+f"(o[i]) :: "memory");
            wg_fence();
            mma_n24_rs<1>(o, p[0], p[1], p[2], p[3], make_desc(vb, 8));
            mma_n24_rs<1>(o, p[4], p[5], p[6], p[7], make_desc(vb + 48, 8));
            mma_n24_rs<1>(o, p[8], p[9], p[10], p[11], make_desc(vb + 96, 8));
            mma_n24_rs<1>(o, p[12], p[13], p[14], p[15], make_desc(vb + 144, 8));
            wg_commit();
            wg_wait<0>();
            #pragma unroll
            for (int i = 0; i < 12; i++) asm volatile("" : "+f"(o[i]) :: "memory");
        }
        attn_store(o, rowbase + mt * 64, head, lane);
    }
}

constexpr int K2_MOVERS = 4;
constexpr int WIMG_DOWN = 96 * 40960;
__device__ __forceinline__ void k2_mover(const CUtensorMap* tmG, const CUtensorMap* tmU, const CUtensorMap* tmD, uint32_t sb) {
    const int tid = threadIdx.x, warp = tid >> 5, lane = tid & 31;
    constexpr int NS = 6, NQ = 3;
    const uint32_t sOut = sb + NS * 24576, barFull = sOut + NQ * 24576, barEmpty = barFull + 8 * NS, barOut = barEmpty + 8 * NS, barFree = barOut + 8 * NQ;
    constexpr int NI = (192 + 80) / K2_MOVERS;
#define K2_TRIG 63
    if (tid == 0) {
        TL(4, 5);
        for (int i = 0; i < NS; i++) { mbar_init(barFull + 8 * i, 1); mbar_init(barEmpty + 8 * i, 12); }
        for (int i = 0; i < NQ; i++) { mbar_init(barOut + 8 * i, 12); mbar_init(barFree + 8 * i, 1); }
        fence_mbar_init();
        fence_async_smem();
    }
    __syncthreads();
    if (warp == 0) {
        if (lane == 0) {
            uint64_t pol;
            asm volatile("createpolicy.fractional.L2::evict_first.b64 %0, 1.0;" : "=l"(pol));
            int s = 0, ph = 1;
            #pragma unroll 1
            for (int n = 0; n < NI; n++) {
                const int id = n * K2_MOVERS + blockIdx.x;
                if (n >= NS) mbar_wait(barEmpty + 8 * s, ph);
                const bool gu = id < 192;
                const CUtensorMap* tm = gu ? (id < 96 ? tmG : tmU) : tmD;
                const int c0 = gu ? ((id % 96) >> 2) * 64 : ((id - 192) >> 3) * 64, c1 = gu ? (id & 3) * 160 : (id & 7) * 192;
                mbar_expect_tx(barFull + 8 * s, gu ? 20480 : 24576);
                asm volatile("cp.async.bulk.tensor.2d.shared::cluster.global.mbarrier::complete_tx::bytes.L2::cache_hint [%0], [%1, {%3, %4}], [%2], %5;"
                    :: "r"(sb + s * 24576), "l"(tm), "r"(barFull + 8 * s), "r"(c0), "r"(c1), "l"(pol) : "memory");
                if (++s == NS) { s = 0; ph ^= 1; }
            }
        }
    } else if (warp == 13) {
        if (lane == 0) {
            int q = 0, ph = 0;
            #pragma unroll 1
            for (int n = 0; n < NI; n++) {
                const int id = n * K2_MOVERS + blockIdx.x;
                const bool gu = id < 192;
                const int u = gu ? (id >= 96 ? id - 96 : id) : id - 192;
                const uint32_t len = gu ? 5120 : 6144;
                uint8_t* dst = g_wimg + (gu ? ((u >> 2) * 32 + (id >= 96 ? 4 : 0) + (u & 3)) * 5120 : WIMG_DOWN + ((u >> 3) * 32 + (u & 7)) * 6144);
                mbar_wait(barOut + 8 * q, ph);
                if (K2_TRIG > 0 && n == K2_TRIG) pdl_launch();
                for (int bl = 0; bl < 4; bl++) bulk_s2g(dst + bl * 8 * len, sOut + q * 24576 + bl * 6144, len);
                bulk_commit();
                asm volatile("cp.async.bulk.wait_group.read 1;" ::: "memory");
                if (n > 0) mbar_arrive(barFree + 8 * (q == 0 ? NQ - 1 : q - 1));
                if (++q == NQ) { q = 0; ph ^= 1; }
            }
            bulk_wait_all();
            TL(4, 6);
        }
    } else if (warp <= 12) {
        const int g = lane >> 2, t = lane & 3, m = (warp - 1) >> 1, h = (warp - 1) & 1;
        const int row = m * 32 + (((g >> 1) & 1) * 4 + t) * 2 + (g >> 2) * 16;
        const uint32_t src = sb + row * 128, sw = (row & 7) ^ (g & 1), dst = sOut + h * 2 * 6144 + m * 1024 + lane * 16;
        int s = 0, ph = 0, q = 0, qh = 1;
        #pragma unroll 1
        for (int n = 0; n < NI; n++) {
            const bool on = n * K2_MOVERS + blockIdx.x >= 192 || m < 5;
            mbar_wait(barFull + 8 * s, ph);
            uint4 u[2], v[2];
            if (on) {
                #pragma unroll
                for (int bl = 0; bl < 2; bl++) {
                    u[bl] = lds_v4(src + s * 24576 + (((h * 4 + bl * 2) ^ sw) << 4));
                    v[bl] = lds_v4(src + 128 + s * 24576 + (((h * 4 + bl * 2) ^ sw ^ 1) << 4));
                }
            }
            if (n >= NQ) mbar_wait(barFree + 8 * q, qh);
            if (on) {
                #pragma unroll
                for (int bl = 0; bl < 2; bl++) {
                    sts_v4(dst + q * 24576 + bl * 6144, make_uint4(u[bl].x, v[bl].x, u[bl].y, v[bl].y));
                    sts_v4(dst + q * 24576 + bl * 6144 + 512, make_uint4(u[bl].z, v[bl].z, u[bl].w, v[bl].w));
                }
            }
            fence_async_smem();
            __syncwarp();
            if (lane == 0) { mbar_arrive(barEmpty + 8 * s); mbar_arrive(barOut + 8 * q); }
            if (++s == NS) { s = 0; ph ^= 1; }
            if (++q == NQ) { q = 0; qh ^= 1; }
        }
    }
}

static_assert((POLYMASK & 0xFF) == (POLYMASK >> 8), "both 64-key tiles of a 128-key block use the same pattern");

__global__ void __launch_bounds__(512, 1)
k2_attn(const __grid_constant__ CUtensorMap tmG, const __grid_constant__ CUtensorMap tmU, const __grid_constant__ CUtensorMap tmD,
        uint32_t cm, uint32_t ce) {
    extern __shared__ __align__(1024) uint8_t smem[];
    if (blockIdx.x < K2_MOVERS) {
        k2_mover(&tmG, &tmU, &tmD, smem_u32(smem));
        return;
    }
    const int bid = blockIdx.x - K2_MOVERS;
    const int head = bid >> 2, quarter = bid & 3;
    const uint32_t sK = smem_u32(smem), sV = sK + HEAD_BYTES, sBar = sK + K2_OFF_BAR, sStg = sK + K2_OFF_STG;
    const int tid = threadIdx.x, wg = tid >> 7, warp = (tid >> 5) & 3, lane = tid & 31, g = lane >> 2, t = lane & 3;
    if (tid == 0) TL(1, 0);
    if (tid == 0) {
        for (int i = 0; i < 9; i++) mbar_init(sBar + i * 8, 1);
        fence_mbar_init();
        fence_async_smem();
        for (int i = 0; i < 4; i++) mbar_expect_tx(sBar + i * 8, 12288);
        mbar_expect_tx(sBar + 32, 4 * 12288);
        mbar_expect_tx(sBar + 40, 12288);
        mbar_expect_tx(sBar + 48, 12288);
        mbar_expect_tx(sBar + 56, 4 * 12288);
        mbar_expect_tx(sBar + 64, 4 * 12288);
    }
    if (tid == 32) sts_v4(sBar + 128, make_uint4(0, 0, 0, 0));
    if (tid >= 64 && tid < 64 + XC_PER) *(uint4*)(g_xc + (bid * XC_PER + tid - 64) * 16) = make_uint4(~0u, ~0u, ~0u, ~0u);
    __syncthreads();
    pdl_wait();
    pdl_launch();
    if (tid == 0) TL(1, 1);
    const uint8_t* Qp = g_qkv + (size_t)head * HEAD_BYTES + (quarter * 64 + wg * 16) * 384;
    const uint8_t* Kp = g_qkv + (size_t)(32 + head) * HEAD_BYTES;
    const uint8_t* Vp = g_qkv + (size_t)(64 + head) * HEAD_BYTES;
    const float4 k4 = __ldcg((const float4*)(g_kmax + head * 128) + lane);
    if (lane == 0) {
        if (warp == 0) bulk_g2s(sStg + wg * 6144, Qp, 3072, sBar + 40);
        const int c = wg * 3 + warp - 1;
        if (warp > 0 && c < K2_FIRST) {
            bulk_g2s(sK + c * 6144, Kp + c * 6144, 6144, sBar + c * 8);
            bulk_g2s(sV + c * 6144, Vp + c * 6144, 6144, sBar + c * 8);
        }
    }
    if (tid == 0) TL(1, 20);
    float km2;
    {
        const uint32_t m = max(max(__float_as_uint(k4.x), __float_as_uint(k4.y)), max(__float_as_uint(k4.z), __float_as_uint(k4.w)));
        km2 = __uint_as_float(__reduce_max_sync(~0u, m));
    }
    if (tid == 0 && km2 >= 0.f) TL(1, 21);
    const int rowbase = quarter * 512 + wg * 128 + warp * 16 + g;
    const bool isaux = (t < 2) == (bool)(head & 1);
    uint32_t q0[8], q1[8];
    mbar_wait(sBar + 40, 0);
    if (tid == 0) TL(1, 17);
    if (lane == 0 && warp == 1 && wg >= K2_FIRST) {
        bulk_g2s(sK + wg * 6144, Kp + wg * 6144, 6144, sBar + wg * 8);
        bulk_g2s(sV + wg * 6144, Vp + wg * 6144, 6144, sBar + wg * 8);
    }
    load_q(sStg, 0, q0);
    uint32_t unsafe = patch_q(q0, km2, isaux, t);
    unsafe = wg_any(unsafe, wg);
    if (tid == 0) TL(1, 16);

    #define GROUP_LOAD(G) do { if (lane == 0 && warp == 2 && wg == (G) + 1) { const uint32_t bar = sBar + ((G) == 0 ? 32 : 48 + 8 * (G)); \
        bulk_g2s(sK + wg * 4 * 6144, Kp + wg * 4 * 6144, 4 * 6144, bar); bulk_g2s(sV + wg * 4 * 6144, Vp + wg * 4 * 6144, 4 * 6144, bar); } } while (0)
    #define Q1_LOAD() do { if (lane == 0 && warp == 3) bulk_g2s(sStg + wg * 6144 + 3072, Qp + 3072, 3072, sBar + 48); } while (0)
    float s[32];
    float o[12];
    uint32_t p[16];
    uint4 qa = make_uint4(q0[0], q0[1], q0[2], q0[3]), qb = make_uint4(q0[4], q0[5], q0[6], q0[7]);
    uint64_t dk, dv;
    #define SET_DESC(KT, VT) do { uint32_t b_; asm volatile("mov.u32 %0, smem;" : "=r"(b_)); \
        dk = make_desc((b_ >> 4) + (KT) * 192 + (8u << 16), 24); dv = make_desc(((b_ + HEAD_BYTES) >> 4) + (VT) * 192 + (24u << 16), 8); } while (0)
    #define ISSUE_QK() do { mma_n64_rs<0>(s, qa.x, qa.y, qa.z, qa.w, dk); mma_n64_rs<1>(s, qb.x, qb.y, qb.z, qb.w, dk + 16); dk += 192; } while (0)
    #define PV(SD) do { mma_n24_rs<SD>(o, p[0], p[1], p[2], p[3], dv); mma_n24_rs<1>(o, p[4], p[5], p[6], p[7], dv + 48); \
                      mma_n24_rs<1>(o, p[8], p[9], p[10], p[11], dv + 96); mma_n24_rs<1>(o, p[12], p[13], p[14], p[15], dv + 144); dv += 192; } while (0)
    constexpr int MA = POLYMASK & 0xFF;
    #define STEP(SD) do { wg_wait<0>(); softmax8<MA>(s, p, cm, ce); wg_fence(); PV(SD); ISSUE_QK(); wg_commit(); } while (0)
    if (!__any_sync(~0u, unsafe)) {
        mbar_wait_warp(sBar, 0);
        if (tid == 0) { TL(1, 2); TLC(1, 5); }
        SET_DESC(0, 0);
        wg_fence();
        ISSUE_QK();
        wg_commit();
        GROUP_LOAD(0);
        Q1_LOAD();
        STEP(0);
        SET_DESC(2, 1);
        #pragma unroll 1
        for (int j = 1; j < 4; j++) {
            mbar_wait_warp(sBar + j * 8, 0);
            STEP(1); STEP(1);
        }
        GROUP_LOAD(1);
        GROUP_LOAD(2);
        if (tid == 0) TLC(1, 18);
        mbar_wait_warp(sBar + 48, 0);
        load_q(sStg, 1, q1);
        unsafe = wg_any(patch_q(q1, km2, isaux, t), wg);
    }
    else { GROUP_LOAD(0); Q1_LOAD(); GROUP_LOAD(1); GROUP_LOAD(2); }
    if (__any_sync(~0u, unsafe)) {
        wg_wait<0>();
        #pragma unroll
        for (int i = 0; i < 32; i++) asm volatile("" : "+f"(s[i]) :: "memory");
        #pragma unroll
        for (int i = 0; i < 12; i++) asm volatile("" : "+f"(o[i]) :: "memory");
        attn_safe(sK, sV, sBar, q0, rowbase, head);
        return;
    }
    #pragma unroll 1
    for (int c = 0; c < 3; c++) {
        mbar_wait_warp(sBar + (c == 0 ? 32 : 48 + 8 * c), 0);
        if (tid == 0 && c == 0) TLC(1, 19);
        SET_DESC(8 + 8 * c, 7 + 8 * c);
        #pragma unroll 1
        for (int j = 0; j < 8 / K2_UNR; j++) { STEP(1); if (K2_UNR > 1) STEP(1); }
    }
    wg_wait<0>();
    qa = make_uint4(q1[0], q1[1], q1[2], q1[3]); qb = make_uint4(q1[4], q1[5], q1[6], q1[7]);
    softmax8<MA>(s, p, cm, ce);
    SET_DESC(0, 31);
    wg_fence();
    PV(1);
    ISSUE_QK();
    wg_commit();
    wg_wait<0>();
    #pragma unroll
    for (int i = 0; i < 12; i++) asm volatile("" : "+f"(o[i]) :: "memory");
    attn_store(o, rowbase, head, lane);
    if ((tid & 127) == 0) TL(1, 8 + wg);
    if (tid == 0) { TL(1, 3); TLC(1, 6); }
    SET_DESC(1, 0);
    STEP(0);
    SET_DESC(2, 1);
    #pragma unroll 1
    for (int j = 0; j < 30 / K2_UNR; j++) { STEP(1); if (K2_UNR > 1) STEP(1); }
    wg_wait<0>();
    softmax8<MA>(s, p, cm, ce);
    SET_DESC(0, 31);
    wg_fence();
    PV(1);
    wg_commit();
    wg_wait<0>();
    #pragma unroll
    for (int i = 0; i < 12; i++) asm volatile("" : "+f"(o[i]) :: "memory");
    attn_store(o, rowbase + 64, head, lane);
    if ((tid & 127) == 0) TL(1, 12 + wg);
    if (tid == 0) { TL(1, 4); TLC(1, 7); }
    #undef SET_DESC
    #undef GROUP_LOAD
    #undef Q1_LOAD
    #undef STEP
    #undef PV
    #undef ISSUE_QK
}

#define K3_WKT 8
#define K3_NPRE 2
constexpr int K3_NB = 7;
constexpr int K3_BT = 20480;
constexpr int K3_OFF_B = 10 * 8192;
constexpr int K3_OFF_BAR = K3_OFF_B + K3_NB * K3_BT;
constexpr int K3_OFF_TOP = K3_OFF_BAR + 256;
constexpr int K3_OFF_SEL = K3_OFF_TOP + 512;
constexpr int K3_OFF_RED = K3_OFF_SEL + 16;
constexpr int K3_OFF_HL = K3_OFF_RED + 1024;
constexpr int K3_XS = 1344, K3_HS = 3136;
constexpr int K3_OFF_X = K3_OFF_HL + 128;
constexpr int K3_SMEM = K3_OFF_X + 2 * K3_XS;
constexpr int K3_OFF_WG = K3_OFF_B + 3 * K3_BT, K3_OFF_WD = 0, K3_OFF_HF = 6 * 8192;

__device__ __forceinline__ uint32_t order_key(float v) {
    const uint32_t u = __float_as_uint(v);
    return u ^ (((int)u >> 31) | 0x80000000u);
}
__device__ __forceinline__ uint32_t row_key(float score, int row) { return (min(order_key(score), 0xFFFFEFFFu) & 0xFFFFF000u) | ((S_ - 1 - row) << 1); }
__device__ __forceinline__ int key_row(uint32_t k) { return S_ - 1 - ((k >> 1) & (S_ - 1)); }
__device__ __forceinline__ void warp_top2(uint32_t& k0, uint32_t& k1) {
    const uint32_t m0 = __reduce_max_sync(~0u, k0);
    k1 = __reduce_max_sync(~0u, k0 == m0 ? k1 : k0);
    k0 = m0;
}
__device__ __forceinline__ uint4 ldx_v4(const void* p) {
    uint4 v; asm volatile("ld.relaxed.gpu.global.v4.b32 {%0,%1,%2,%3}, [%4];" : "=r"(v.x), "=r"(v.y), "=r"(v.z), "=r"(v.w) : "l"(p) : "memory"); return v;
}
__device__ __forceinline__ void stx_v4(void* p, uint32_t a, uint32_t b, uint32_t c, uint32_t d, bool on) {
    asm volatile("{\n.reg .pred p;\nsetp.ne.u32 p, %5, 0;\n@p st.relaxed.gpu.global.v4.b32 [%0], {%1,%2,%3,%4};\n}\n"
        :: "l"(p), "r"(a), "r"(b), "r"(c), "r"(d), "r"((uint32_t)on) : "memory");
}
__device__ __forceinline__ void st_v4(void* p, uint32_t a, uint32_t b, uint32_t c, uint32_t d, bool on) {
    asm volatile("{\n.reg .pred p;\nsetp.ne.u32 p, %5, 0;\n@p st.global.v4.b32 [%0], {%1,%2,%3,%4};\n}\n"
        :: "l"(p), "r"(a), "r"(b), "r"(c), "r"(d), "r"((uint32_t)on) : "memory");
}
__device__ __forceinline__ bool valid4(const uint4 v) { return v.x != ~0u && v.y != ~0u && v.z != ~0u && v.w != ~0u; }
template<int NL>
__device__ __forceinline__ void poll(const uint8_t* p, uint32_t stride, uint4 (&r)[NL]) {
    uint32_t it = 0;
    bool ok;
    do {
        ok = true;
        #pragma unroll
        for (int l = 0; l < NL; l++) r[l] = ldx_v4(p + l * stride);
        #pragma unroll
        for (int l = 0; l < NL; l++) ok = ok && valid4(r[l]);
        if (++it > (1u << 22)) __trap();
    } while (!__all_sync(~0u, ok));
}
__device__ __forceinline__ uint32_t lds_flag(uint32_t a) { uint32_t v; asm volatile("ld.acquire.cta.shared.b32 %0, [%1];" : "=r"(v) : "r"(a) : "memory"); return v; }
__device__ __forceinline__ void sts_flag(uint32_t a) { asm volatile("st.release.cta.shared.b32 [%0], %1;" :: "r"(a), "r"(1) : "memory"); }
__device__ __forceinline__ void wait_flag(uint32_t a) { uint32_t it = 0; while (!lds_flag(a)) { if (++it > (1u << 26)) __trap(); } }
__device__ __forceinline__ void pause(uint32_t cycles) { const uint32_t c0 = clock(); while (clock() - c0 < cycles) {} }
#define K3_EARLY 0
#define K3_PACE 100
#define K3_PACE0 500
#define K3_KPOLL 1
#define K3_KGAP 270
__device__ __forceinline__ uint32_t hadd_bf2(uint32_t a, uint32_t b) {
    uint32_t r; asm("add.rn.bf16x2 %0, %1, %2;" : "=r"(r) : "r"(a), "r"(b)); return r;
}
template<int NB>
__device__ __forceinline__ void gemv16(const uint4 (&w)[2 * NB], uint32_t xs, uint32_t pitch, float* red, int lane) {
    const int g = lane >> 2, t = lane & 3;
    const uint32_t xa = xs + ((g >> 1) & 1) * pitch + ((g >> 2) * 4 + t) * 4;
    const uint32_t selLo = (g & 1) ? 0x1044u : 0x4410u, selHi = (g & 1) ? 0x3244u : 0x4432u;
    float c[4][4];
    #pragma unroll
    for (int j = 0; j < 4; j++) { c[j][0] = 0.f; c[j][1] = 0.f; c[j][2] = 0.f; c[j][3] = 0.f; }
    uint32_t x0[NB], x1[NB];
    #pragma unroll
    for (int i = 0; i < NB; i++) {
        asm volatile("ld.shared.b32 %0, [%1];" : "=r"(x0[i]) : "r"(xa + 64 * i) : "memory");
        asm volatile("ld.shared.b32 %0, [%1];" : "=r"(x1[i]) : "r"(xa + 64 * i + 32) : "memory");
    }
    #pragma unroll
    for (int i = 0; i < NB; i++) {
        const uint32_t a0 = __byte_perm(x0[i], 0, selLo), a2 = __byte_perm(x0[i], 0, selHi), a1 = __byte_perm(x1[i], 0, selLo), a3 = __byte_perm(x1[i], 0, selHi);
        const uint32_t b0[4] = {w[2 * i].x, w[2 * i].z, w[2 * i + 1].x, w[2 * i + 1].z}, b1[4] = {w[2 * i].y, w[2 * i].w, w[2 * i + 1].y, w[2 * i + 1].w};
        #pragma unroll
        for (int j = 0; j < 4; j++)
            asm volatile("mma.sync.aligned.m16n8k16.row.col.f32.bf16.bf16.f32 {%0,%1,%2,%3}, {%4,%5,%6,%7}, {%8,%9}, {%0,%1,%2,%3};"
                : "+f"(c[j][0]), "+f"(c[j][1]), "+f"(c[j][2]), "+f"(c[j][3]) : "r"(a0), "r"(a1), "r"(a2), "r"(a3), "r"(b0[j]), "r"(b1[j]));
    }
    float v[4];
    #pragma unroll
    for (int j = 0; j < 4; j++) {
        const float keep = t < 2 ? c[j][0] : c[j][3], send = t < 2 ? c[j][1] : c[j][2];
        v[j] = keep + __shfl_xor_sync(~0u, send, 2);
    }
    const bool odd = t & 1;
    const float e0 = (odd ? v[2] : v[0]) + __shfl_xor_sync(~0u, odd ? v[0] : v[2], 17);
    const float e1 = (odd ? v[3] : v[1]) + __shfl_xor_sync(~0u, odd ? v[1] : v[3], 17);
    if ((t & 1) == (g >> 2)) {
        float* r = red + (((g >> 1) & 1) * 16 + (t >> 1) * 8 + (t & 1) * 4 + (g & 1)) * 8;
        r[0] = e0; r[16] = e1;
    }
}

__global__ void __launch_bounds__(384, 1)
k3_tail(const __grid_constant__ CUtensorMap tmR, const bf16* __restrict__ wr, bf16* __restrict__ out) {
    extern __shared__ __align__(1024) uint8_t smem[];
    const uint32_t sb = smem_u32(smem);
    uint32_t barFull = sb + K3_OFF_BAR;
    const int tid = threadIdx.x, warp = tid >> 5, lane = tid & 31, b = blockIdx.x;
    const int nt = b & 3, mt = b >> 2;
    const int g = lane >> 2, t = lane & 3;
    if (warp < 4) {
        float acc[80], wv[40], wsum;
        cluster_arrive();
        const uint32_t hiA = 8u, hiB = 8u;
        const uint32_t sa = __reduce_max_sync(~0u, (sb & 0x3FFFF) >> 4);
        uint4 xa[5], xb[5], wp[5];
        if (tid == 0) TL(2, 7);
        cluster_wait();
        mbar_wait_warp(barFull + 120, 0);
        #pragma unroll
        for (int J = 0; J < 5; J++) {
            const uint32_t xs = sb + K3_OFF_B + (K3_NB - 1) * K3_BT + (warp * 16 + g) * 320 + 16 * t + 64 * J;
            xa[J] = lds_v4(xs); xb[J] = lds_v4(xs + 8 * 320); wp[J] = lds_v4(sb + K3_OFF_RED + 16 * t + 64 * J);
        }
        wsum = 0.f;
        #pragma unroll
        for (int J = 0; J < 5; J++) {
            const uint32_t xw0[4] = {xa[J].x, xa[J].y, xa[J].z, xa[J].w}, xw1[4] = {xb[J].x, xb[J].y, xb[J].z, xb[J].w};
            const uint32_t ww[4] = {wp[J].x, wp[J].y, wp[J].z, wp[J].w};
            #pragma unroll
            for (int jj = 0; jj < 4; jj++) {
                const int j = 4 * J + jj;
                acc[4 * j] = bf_lo(xw0[jj]); acc[4 * j + 1] = bf_hi(xw0[jj]); acc[4 * j + 2] = bf_lo(xw1[jj]); acc[4 * j + 3] = bf_hi(xw1[jj]);
                wv[2 * j] = bf_lo(ww[jj]); wv[2 * j + 1] = bf_hi(ww[jj]);
                wsum += wv[2 * j] + wv[2 * j + 1];
            }
        }
        wsum += __shfl_xor_sync(~0u, wsum, 1);
        wsum += __shfl_xor_sync(~0u, wsum, 2);
        asm volatile("" : "+f"(wsum));
        #pragma unroll
        for (int i = 0; i < 40; i++) asm volatile("" : "+f"(wv[i]));
        #pragma unroll
        for (int i = 0; i < 80; i++) asm volatile("" : "+f"(acc[i]) :: "memory");
        asm volatile("" : "+r"(barFull));
        if (lane == 0) mbar_arrive(barFull + 128);
        pdl_wait();
        #pragma unroll 1
        for (int kt = 0; kt < 10; kt++) {
            mbar_wait_warp(barFull + 8 * kt, 0);
            if (tid == 0 && kt == 0) TL(2, 2);
            const int slot = kt < K3_NB ? kt : kt - K3_NB;
            const uint32_t loA = sa + kt * 512 + (64u << 16), loB = sa + (K3_OFF_B >> 4) + slot * (K3_BT >> 4) + (160u << 16);
            wg_fence();
            #pragma unroll
            for (int kk = 0; kk < 4; kk++)
                mma_n160_ss(acc, make_desc(loA + 128 * kk, hiA), make_desc(loB + 320 * kk, hiB), 1);
            wg_commit();
            if (((0xE | (K3_WKT < 10 ? 1 << (K3_WKT - 1) : 0)) >> kt) & 1) {
                wg_wait<1>();
                if (lane == 0) mbar_arrive(barFull + 80 + 8 * min(kt - 1, 3));
            }
        }
        wg_wait<0>();
        if (K3_WKT == 10 && lane == 0) mbar_arrive(barFull + 104);
        #pragma unroll
        for (int i = 0; i < 80; i++) asm volatile("" : "+f"(acc[i]) :: "memory");
        if (tid == 0) { TL(2, 3); TLC(3, 16); }

        const int r0 = mt * 64 + warp * 16 + g;
        float s0 = 0.f, q0 = 0.f, d0 = 0.f, s1 = 0.f, q1 = 0.f, d1 = 0.f;
        #pragma unroll
        for (int j = 0; j < 20; j++) {
            const float a0 = acc[4 * j], a1 = acc[4 * j + 1], b0 = acc[4 * j + 2], b1 = acc[4 * j + 3];
            s0 += a0 + a1; q0 = fmaf(a0, a0, fmaf(a1, a1, q0)); d0 = fmaf(a0, wv[2 * j], fmaf(a1, wv[2 * j + 1], d0));
            s1 += b0 + b1; q1 = fmaf(b0, b0, fmaf(b1, b1, q1)); d1 = fmaf(b0, wv[2 * j], fmaf(b1, wv[2 * j + 1], d1));
        }
        #pragma unroll
        for (int o = 1; o < 4; o <<= 1) {
            s0 += __shfl_xor_sync(~0u, s0, o); q0 += __shfl_xor_sync(~0u, q0, o); d0 += __shfl_xor_sync(~0u, d0, o);
            s1 += __shfl_xor_sync(~0u, s1, o); q1 += __shfl_xor_sync(~0u, q1, o); d1 += __shfl_xor_sync(~0u, d1, o);
        }
        uint8_t* part = g_xc + XC_PART + mt * 4096 + (warp * 16 + g) * 16;
        stx_v4(part + (t & 1) * 128 + nt * 1024, __float_as_uint(t & 1 ? s1 : s0), __float_as_uint(t & 1 ? q1 : q0), __float_as_uint(t & 1 ? d1 : d0),
               __float_as_uint(wsum), t < 2);
        if (K3_WKT == 12 && lane == 0) mbar_arrive(barFull + 104);
        if (tid == 0) { TL(2, 4); TLC(3, 17); }
        uint4 pr[2];
        poll(part + t * 1024, 128, pr);
        const uint4 ua = pr[0], ub = pr[1];
        if (K3_WKT == 11 && lane == 0) mbar_arrive(barFull + 104);
        if (tid == 0) { TL(2, 5); TLC(3, 18); }
        s0 = __uint_as_float(ua.x); q0 = __uint_as_float(ua.y); d0 = __uint_as_float(ua.z);
        s1 = __uint_as_float(ub.x); q1 = __uint_as_float(ub.y); d1 = __uint_as_float(ub.z);
        float ws = __uint_as_float(ua.w);
        #pragma unroll
        for (int o = 1; o < 4; o <<= 1) {
            s0 += __shfl_xor_sync(~0u, s0, o); q0 += __shfl_xor_sync(~0u, q0, o); d0 += __shfl_xor_sync(~0u, d0, o);
            s1 += __shfl_xor_sync(~0u, s1, o); q1 += __shfl_xor_sync(~0u, q1, o); d1 += __shfl_xor_sync(~0u, d1, o);
            ws += __shfl_xor_sync(~0u, ws, o);
        }
        const float mua = s0 * (1.f / D_), mub = s1 * (1.f / D_);
        const float rsa = rsqrtf(fmaxf(q0 * (1.f / D_) - mua * mua, 0.f) + 1e-5f), rsb = rsqrtf(fmaxf(q1 * (1.f / D_) - mub * mub, 0.f) + 1e-5f);
        uint2* s_top = (uint2*)(smem + K3_OFF_TOP);
        if (t < 2) {
            const float score = t == 0 ? rsa * (d0 - mua * ws) : rsb * (d1 - mub * ws);
            s_top[warp * 16 + g + 8 * t] = make_uint2(row_key(score, r0 + 8 * t), __float_as_uint(score));
        }
        if (tid == 0) TLC(3, 20);
        named_bar<3, 128>();
        if (tid == 0) TLC(3, 21);
        const uint4 tv = ((const uint4*)s_top)[lane];
        uint32_t k0 = max(tv.x, tv.z), k1 = min(tv.x, tv.z);
        warp_top2(k0, k1);
        const int i0 = key_row(k0), i1 = key_row(k1);
        if (tid < K3_KW) stx_v4(g_xc + XC_KEYS + (nt * 32 + mt) * (16 * K3_KW) + tid * 16, k0, k1 | 1, s_top[i0 & 63].y, s_top[i1 & 63].y, true);
        if (tid == 0) { TL(2, 9); TLC(3, 22); }
        const bool ca = r0 == i0 || r0 == i1, cb = r0 + 8 == i0 || r0 + 8 == i1;
        uint8_t* cpa = g_xc + XC_CAND + (mt * 2 + (r0 == i1)) * 2560 + (nt * 160 + 8 * t) * 2;
        uint8_t* cpb = g_xc + XC_CAND + (mt * 2 + (r0 + 8 == i1)) * 2560 + (nt * 160 + 8 * t) * 2;
        bf16* o0 = out + (size_t)r0 * D_ + nt * 160 + 8 * t;
        const float ma = -mua * rsa, mb = -mub * rsb;
        uint32_t oa[20], ob[20];
        #pragma unroll
        for (int J = 0; J < 5; J++) {
            uint32_t ha[4], hb[4], la[4], lb[4];
            #pragma unroll
            for (int jj = 0; jj < 4; jj++) {
                const int j = 4 * J + jj;
                ha[jj] = pack_bf(acc[4 * j], acc[4 * j + 1]); hb[jj] = pack_bf(acc[4 * j + 2], acc[4 * j + 3]);
                la[jj] = pack_bf(fmaf(acc[4 * j], rsa, ma), fmaf(acc[4 * j + 1], rsa, ma));
                lb[jj] = pack_bf(fmaf(acc[4 * j + 2], rsb, mb), fmaf(acc[4 * j + 3], rsb, mb));
                oa[j] = hadd_bf2(ha[jj], la[jj]); ob[j] = hadd_bf2(hb[jj], lb[jj]);
            }
            stx_v4(cpa + 64 * J, la[0], la[1], la[2], la[3], ca);
            stx_v4(cpb + 64 * J, lb[0], lb[1], lb[2], lb[3], cb);
            stx_v4(cpa + 64 * J + 1280, ha[0], ha[1], ha[2], ha[3], ca);
            stx_v4(cpb + 64 * J + 1280, hb[0], hb[1], hb[2], hb[3], cb);
        }
        if (tid == 0) { TL(2, 8); TLC(3, 23); }
        wait_flag(barFull + 192);
        const uint2 sel = *(const uint2*)(smem + K3_OFF_SEL);
        const int row0 = key_row(sel.x), row1 = key_row(sel.y);
        const bool wa = (ca || !K3_EARLY) && r0 != row0 && r0 != row1, wb = (cb || !K3_EARLY) && r0 + 8 != row0 && r0 + 8 != row1;
        #pragma unroll
        for (int J = 0; J < 5; J++) {
            if (J ? K3_PACE : K3_PACE0) pause(J ? K3_PACE : K3_PACE0);
            st_v4(o0 + 32 * J, oa[4 * J], oa[4 * J + 1], oa[4 * J + 2], oa[4 * J + 3], wa);
            st_v4(o0 + 8 * D_ + 32 * J, ob[4 * J], ob[4 * J + 1], ob[4 * J + 2], ob[4 * J + 3], wb);
        }
        if (tid == 0) TL(2, 6);
        return;
    }
    if (warp == 11) {
        const uint8_t* img = g_wo_img + nt * (10 * K3_BT);
        const uint32_t barEmpty = barFull + 80;
        if (lane == 0) {
            TL(2, 0);
            tmap_prefetch(&tmR);
            for (int i = 0; i < 10; i++) mbar_init(barFull + 8 * i, 1);
            for (int i = 0; i < 4; i++) mbar_init(barEmpty + 8 * i, 4);
            mbar_init(barFull + 112, 1);
            mbar_init(barFull + 120, 1);
            mbar_init(barFull + 128, 4);
            asm volatile("st.shared.b32 [%0], %1;\nfence.acq_rel.cta;" :: "r"(barFull + 192), "r"(0) : "memory");
            fence_mbar_init();
            fence_async_smem();
            for (int i = 0; i < 10; i++) mbar_expect_tx(barFull + 8 * i, 8192 + K3_BT);
            mbar_expect_tx(barFull + 112, (b < 96 ? 40960 : 0) + (b >= 88 ? 49152 : 0));
            mbar_expect_tx(barFull + 120, K3_BT + 320);
            tma_2d(sb + K3_OFF_B + (K3_NB - 1) * K3_BT, &tmR, nt * 160, mt * 64, barFull + 120);
            bulk_g2s(sb + K3_OFF_RED, wr + nt * 160, 320, barFull + 120);
            for (int kt = 0; kt < K3_NPRE; kt++) bulk_g2s(sb + K3_OFF_B + kt * K3_BT, img + kt * K3_BT, K3_BT, barFull + 8 * kt);
        }
        __syncwarp();
        cluster_arrive();
        cluster_wait();
        if (lane == 0) {
            uint32_t rank; asm("mov.u32 %0, %%cluster_ctarank;" : "=r"(rank));
            pdl_wait();
            TL(2, 1);
            #pragma unroll 1
            for (int kt = 0; kt < 10; kt++) {
                if ((kt & 1) == (int)rank) bulk_g2s_mc(sb + kt * 8192, (const uint8_t*)g_o + mt * 81920 + kt * 8192, 8192, barFull + 8 * kt, (uint16_t)3);
                if (kt == K3_NB - 1) mbar_wait(barFull + 128, 0);
                if (kt >= K3_NPRE && kt < K3_NB) bulk_g2s(sb + K3_OFF_B + kt * K3_BT, img + kt * K3_BT, K3_BT, barFull + 8 * kt);
            }
            #pragma unroll 1
            for (int j = 0; j < 10 - K3_NB; j++) {
                mbar_wait(barEmpty + 8 * j, 0);
                bulk_g2s(sb + K3_OFF_B + j * K3_BT, img + (K3_NB + j) * K3_BT, K3_BT, barFull + 8 * (K3_NB + j));
            }
            if (b == 0) g_epoch = g_epoch + 1;
            mbar_wait(barEmpty + 24, 0);
            TL(3, 0);
            if (b < 96) bulk_g2s(sb + K3_OFF_WG, g_wimg + b * 40960, 40960, barFull + 112);
            if (b >= 88) bulk_g2s(sb + K3_OFF_WD, g_wimg + WIMG_DOWN + (b - 88) * 49152, 49152, barFull + 112);
        }
        __syncwarp();
    } else {
        cluster_arrive();
        cluster_wait();
    }

    const int tt = tid - 128, tw = warp - 4;
    if (tt == 0) TL(3, 5);
    float* s_red = (float*)(smem + K3_OFF_RED);
    mbar_wait_warp(barFull + 112, 0);
    if (tt == 0) TL(3, 6);
    uint4 wA[10], wB[12];
    if (b < 96) {
        #pragma unroll
        for (int i = 0; i < 10; i++) wA[i] = lds_v4(sb + K3_OFF_WG + tw * 5120 + i * 512 + lane * 16);
    }
    if (b >= 88) {
        #pragma unroll
        for (int i = 0; i < 12; i++) wB[i] = lds_v4(sb + K3_OFF_WD + tw * 6144 + i * 512 + lane * 16);
    }
    pdl_wait();
    if (tw >= 8 - K3_KPOLL) {
        pause((7 - tw) * K3_KGAP);
        uint4 kv;
        uint32_t it = 0;
        bool ok;
        do {
            kv = ldx_v4(g_xc + XC_KEYS + (nt * 32 + lane) * (16 * K3_KW));
            ok = __all_sync(~0u, valid4(kv));
            if (++it > (1u << 22)) __trap();
        } while (!ok && !lds_flag(barFull + 192));
        if (ok) {
            if (lane == 0) { TL(3, 1); TLC(4, 24); }
            uint32_t k0 = kv.x, k1 = kv.y;
            warp_top2(k0, k1);
            uint32_t* sel = (uint32_t*)(smem + K3_OFF_SEL);
            if (lane == 0) { sel[0] = k0; sel[1] = k1; }
            if (kv.x == k0) sel[2] = kv.z;
            if (kv.y == k0) sel[2] = kv.w;
            if (kv.x == k1) sel[3] = kv.z;
            if (kv.y == k1) sel[3] = kv.w;
            __syncwarp();
            if (lane == 0) sts_flag(barFull + 192);
        }
    }
    wait_flag(barFull + 192);
    if (tt == 0) { TL(3, 2); TLC(4, 25); }
    const uint4 sel = *(const uint4*)(smem + K3_OFF_SEL);
    {
        const int u = tt - 160, tk = tt < 160 ? tt >= 80 : (u >> 2) & 1;
        const uint32_t j = tk ? sel.y : sel.x;
        const uint32_t off = tt < 160 ? (tt - 80 * tk) * 16 : ((u >> 1) & 1) * 1280 + max(b - 88, 0) * 32 + (u & 1) * 16;
        const uint32_t dst = tt < 160 ? sb + K3_OFF_X + tk * K3_XS + off : sb + K3_OFF_HL + (u & 7) * 16;
        const uint8_t* src = g_xc + XC_CAND + ((key_row(j) >> 6) * 2 + (j & 1)) * 2560 + off;
        const bool on = tt < 160 ? b < 96 : (tt < 168 && b >= 88);
        if (on) {
            uint4 v;
            uint32_t it = 0;
            do {
                v = ldx_v4(src);
                if (++it > (1u << 22)) __trap();
            } while (!valid4(v));
            sts_v4(dst, v);
        }
    }
    named_bar<1, 256>();
    if (tt == 0) { TL(3, 3); TLC(4, 20); }
    if (b < 96) {
        gemv16<5>(wA, sb + K3_OFF_X + (tw & 3) * 320, K3_XS, s_red + tw, lane);
        if (tt == 0) TLC(4, 21);
        named_bar<1, 256>();
        if (tt == 0) TLC(4, 22);
        if (tt < 32) {
            const float4 pg = ((const float4*)s_red)[2 * tt], pu = ((const float4*)s_red)[2 * tt + 1];
            const float gb = round_bf((pg.x + pg.y) + (pg.z + pg.w));
            const float ub = round_bf((pu.x + pu.y) + (pu.z + pu.w));
            const float sl = round_bf(__fdividef(gb, 1.f + ex2(-1.4426950409f * gb)));
            const float v = sl * ub, vn = __shfl_down_sync(~0u, v, 1);
            if (!(tt & 1))
                asm volatile("st.relaxed.gpu.global.b32 [%0], %1;" :: "l"(g_xc + XC_HF + (tt >> 4) * (F_ * 2) + (b * 16 + (tt & 15)) * 2), "r"(pack_bf(v, vn)) : "memory");
            if (tt == 0) { TL(3, 4); TLC(4, 23); }
        }
    }
    if (b >= 88) {
        uint4 hv[2];
        poll(g_xc + XC_HF + tt * 16, tt < 128 ? 4096 : 0, hv);
        sts_v4(sb + K3_OFF_HF + (tt >= 192 ? K3_HS - F_ * 2 : 0) + tt * 16, hv[0]);
        if (tt < 128) sts_v4(sb + K3_OFF_HF + K3_HS - F_ * 2 + 4096 + tt * 16, hv[1]);
        const float rsel = round_bf(__uint_as_float((tt >> 4) & 1 ? sel.w : sel.z));
        const float sg = round_bf(__fdividef(1.f, 1.f + ex2(-1.4426950409f * rsel)));
        named_bar<1, 256>();
        if (tt == 0) { TL(4, 1); TLC(4, 16); }
        gemv16<6>(wB, sb + K3_OFF_HF + tw * 384, K3_HS, s_red + tw, lane);
        if (tt == 0) TLC(4, 17);
        named_bar<1, 256>();
        if (tt == 0) TLC(4, 18);
        if (tt < 32) {
            const int tk = tt >> 4;
            const float4 pa = ((const float4*)s_red)[2 * tt], pb = ((const float4*)s_red)[2 * tt + 1];
            const float y = ((pa.x + pa.y) + (pa.z + pa.w)) + ((pb.x + pb.y) + (pb.z + pb.w));
            const bf16* hl = (const bf16*)(smem + K3_OFF_HL) + tk * 32 + (tt & 15);
            const float ln = __bfloat162float(hl[0]), h = __bfloat162float(hl[16]);
            const float upd = round_bf(round_bf(y) * sg);
            out[(size_t)key_row(tk ? sel.y : sel.x) * D_ + (b - 88) * 16 + (tt & 15)] = __float2bfloat16_rn(h + round_bf(ln + upd));
            if (tt == 0) { TL(4, 2); TLC(4, 19); }
        }
    }
}

#define EXP_PROMO CU_TENSOR_MAP_L2_PROMOTION_L2_256B
typedef CUresult (*PFN_encodeTiled)(CUtensorMap*, CUtensorMapDataType, cuuint32_t, void*, const cuuint64_t*, const cuuint64_t*, const cuuint32_t*,
                                    const cuuint32_t*, CUtensorMapInterleave, CUtensorMapSwizzle, CUtensorMapL2promotion, CUtensorMapFloatOOBfill);

static void encode_map(PFN_encodeTiled fn, CUtensorMap* m, const void* base, int rank, const cuuint64_t* dims, const cuuint64_t* strides,
                       const cuuint32_t* box, CUtensorMapSwizzle sw, CUtensorMapL2promotion promo = EXP_PROMO) {
    cuuint32_t es[3] = {1, 1, 1};
    fn(m, CU_TENSOR_MAP_DATA_TYPE_BFLOAT16, rank, (void*)base, dims, strides, box, es, CU_TENSOR_MAP_INTERLEAVE_NONE, sw,
       promo, CU_TENSOR_MAP_FLOAT_OOB_FILL_NONE);
}

template <typename... KArgs, typename... Args>
static void launch(void (*kern)(KArgs...), int grid, int block, int smem, int cluster, bool pdl, Args... args) {
    cudaLaunchConfig_t cfg = {};
    cfg.gridDim = dim3(grid); cfg.blockDim = dim3(block); cfg.dynamicSmemBytes = smem; cfg.stream = cudaStreamPerThread;
    cudaLaunchAttribute at[2]; int n = 0;
    if (cluster > 1) { at[n].id = cudaLaunchAttributeClusterDimension; at[n].val.clusterDim.x = cluster; at[n].val.clusterDim.y = 1; at[n].val.clusterDim.z = 1; n++; }
    if (pdl) { at[n].id = cudaLaunchAttributeProgrammaticStreamSerialization; at[n].val.programmaticStreamSerializationAllowed = 1; n++; }
    cfg.attrs = at; cfg.numAttrs = n;
    cudaLaunchKernelEx(&cfg, kern, args...);
}

extern "C" void kernel_launch(void* const* d_in, const int* in_sizes, int n_in, void* d_out, int out_size) {
    const bf16* x = (const bf16*)d_in[0];
    const bf16* wqkv = (const bf16*)d_in[1];
    const bf16* wo = (const bf16*)d_in[2];
    const bf16* wr = (const bf16*)d_in[4];
    const bf16* wgate = (const bf16*)d_in[5];
    const bf16* wup = (const bf16*)d_in[6];
    const bf16* wdown = (const bf16*)d_in[7];
    bf16* out = (bf16*)d_out;

    static PFN_encodeTiled enc = nullptr;
    if (!enc) {
        cudaDriverEntryPointQueryResult qr;
        void* fn = nullptr;
        cudaGetDriverEntryPoint("cuTensorMapEncodeTiled", &fn, cudaEnableDefault, &qr);
        enc = (PFN_encodeTiled)fn;
        cudaFuncSetAttribute(k1_qkv, cudaFuncAttributeMaxDynamicSharedMemorySize, K1_SMEM);
        cudaFuncSetAttribute(k2_attn, cudaFuncAttributeMaxDynamicSharedMemorySize, K2_SMEM);
        cudaFuncSetAttribute(k3_tail, cudaFuncAttributeMaxDynamicSharedMemorySize, K3_SMEM);
    }
    CUtensorMap tmX, tmW, tmG, tmU, tmD, tmR;
    { cuuint64_t d[2] = {640, 2048}, s[1] = {1280}; cuuint32_t b[2] = {160, 64}; encode_map(enc, &tmR, x, 2, d, s, b, CU_TENSOR_MAP_SWIZZLE_NONE); }
    { cuuint64_t d[2] = {640, 2048}, s[1] = {1280}; cuuint32_t b[2] = {64, 128}; encode_map(enc, &tmX, x, 2, d, s, b, CU_TENSOR_MAP_SWIZZLE_128B); }
    { cuuint64_t d[2] = {1920, 640}, s[1] = {3840}; cuuint32_t b[2] = {64, 64}; encode_map(enc, &tmW, wqkv, 2, d, s, b, CU_TENSOR_MAP_SWIZZLE_128B); }

    { cuuint64_t d[2] = {1536, 640}, s[1] = {3072}; cuuint32_t b[2] = {64, 160}; encode_map(enc, &tmG, wgate, 2, d, s, b, CU_TENSOR_MAP_SWIZZLE_128B);
      encode_map(enc, &tmU, wup, 2, d, s, b, CU_TENSOR_MAP_SWIZZLE_128B); }
    { cuuint64_t d[2] = {640, 1536}, s[1] = {1280}; cuuint32_t b[2] = {64, 192}; encode_map(enc, &tmD, wdown, 2, d, s, b, CU_TENSOR_MAP_SWIZZLE_128B); }

    launch(k1_qkv, 128, 384, K1_SMEM, 2, false, tmX, tmW, x, wqkv, wo);
    launch(k2_attn, 128 + K2_MOVERS, 512, K2_SMEM, 1, true, tmG, tmU, tmD, 0x007F007Fu, 0xFF80FF80u);
    launch(k3_tail, 128, 384, K3_SMEM, 2, true, tmR, wr, out);
}
```
